```python
import torch

def _softmax(x, axis=-1):
    return torch.softmax(x, dim=axis)
def _gelu(x):
    return torch.nn.functional.gelu(x, approximate="tanh")
def _silu(x):
    return torch.nn.functional.silu(x)
def _sigmoid(x):
    return torch.sigmoid(x)
def _layernorm(x, axis=-1, eps=1e-5):
    m = x.mean(dim=axis, keepdim=True)
    v = x.var(dim=axis, keepdim=True, unbiased=False)
    return (x - m) / torch.sqrt(v + eps)
def _scatter_add(tgt, idx, src, axis=0):
    return tgt.clone().index_add_(axis, idx, src)
def _segment_sum(src, seg, n):
    out = torch.zeros((n,) + src.shape[1:], dtype=src.dtype)
    return out.index_add_(0, seg, src)
def _pad(x, pw):
    flat = tuple(v for pair in reversed(pw) for v in pair)
    return torch.nn.functional.pad(x, flat)

kernel_name = 'gated_mix__grouped_kv_mqa__grouped_kv_mqa__prompt'

def setup_inputs():

    _w = (lambda a: (lambda t: t.to(torch.bfloat16) if t.is_floating_point() else t)(torch.as_tensor(a)))
    def _A_setup():
        B, S, D, H = 1, 2048, 512, 32
        Dh = D // H
        return {
            "x": _w((lambda *s: torch.randn(*s, dtype=torch.bfloat16) * 0.05)(B, S, D)),
            "wq": _w((lambda *s: torch.randn(*s, dtype=torch.bfloat16) * 0.8)(D, H * Dh)),
            "wk": _w((lambda *s: torch.randn(*s, dtype=torch.bfloat16) * 0.8)(D, Dh)),
            "wv": _w((lambda *s: torch.randn(*s, dtype=torch.bfloat16) * 0.05)(D, Dh)),
            "wo": _w((lambda *s: torch.randn(*s, dtype=torch.bfloat16) * 0.05)(H * Dh, D)),
        }
    _A_in = _A_setup()

    def _B_setup():
        B, S, D, H = 1, 2048, 512, 32
        Dh = D // H
        return {
            "x": _w((lambda *s: torch.randn(*s, dtype=torch.bfloat16) * 0.05)(B, S, D)),
            "wq": _w((lambda *s: torch.randn(*s, dtype=torch.bfloat16) * 0.8)(D, H * Dh)),
            "wk": _w((lambda *s: torch.randn(*s, dtype=torch.bfloat16) * 0.8)(D, Dh)),
            "wv": _w((lambda *s: torch.randn(*s, dtype=torch.bfloat16) * 0.05)(D, Dh)),
            "wo": _w((lambda *s: torch.randn(*s, dtype=torch.bfloat16) * 0.05)(H * Dh, D)),
        }
    _B_in = _B_setup()

    return {
        "A_x": _A_in["x"],
        "A_wq": _A_in["wq"],
        "A_wk": _A_in["wk"],
        "A_wv": _A_in["wv"],
        "A_wo": _A_in["wo"],
        "B_x": _B_in["x"],
        "B_wq": _B_in["wq"],
        "B_wk": _B_in["wk"],
        "B_wv": _B_in["wv"],
        "B_wo": _B_in["wo"],
        "gate_w": _w((lambda *s: torch.randn(*s, dtype=torch.bfloat16) * 0.05)(512) * 16.0),
    }

def reference(A_x, A_wq, A_wk, A_wv, A_wo, B_x, B_wq, B_wk, B_wv, B_wo, gate_w):
    def _A_ref(x, wq, wk, wv, wo):
        B, S, D = x.shape
        H = 32
        Dh = D // H
        q = (lambda x, *d: x.permute(*d))((x @ wq).reshape(B, S, H, Dh), 0, 2, 1, 3)
        k = x @ wk
        v = x @ wv
        scores = torch.einsum("bhqd,bkd->bhqk", q, k) * (Dh ** -0.5)
        p = _softmax(scores, axis=-1)
        o = torch.einsum("bhqk,bkd->bhqd", p, v)
        return (lambda x, *d: x.permute(*d))(o, 0, 2, 1, 3).reshape(B, S, H * Dh) @ wo

    def _B_ref(x, wq, wk, wv, wo):
        B, S, D = x.shape
        H = 32
        Dh = D // H
        q = (lambda x, *d: x.permute(*d))((x @ wq).reshape(B, S, H, Dh), 0, 2, 1, 3)
        k = x @ wk
        v = x @ wv
        scores = torch.einsum("bhqd,bkd->bhqk", q, k) * (Dh ** -0.5)
        p = _softmax(scores, axis=-1)
        o = torch.einsum("bhqk,bkd->bhqd", p, v)
        return (lambda x, *d: x.permute(*d))(o, 0, 2, 1, 3).reshape(B, S, H * Dh) @ wo

    x = A_x
    g = _sigmoid((x * gate_w).sum(-1, keepdims=True))
    a = _A_ref(x, A_wq, A_wk, A_wv, A_wo)
    b = _B_ref(x, B_wq, B_wk, B_wv, B_wo)
    return g * a + (1 - g) * b
```

```cpp
#include <cuda_runtime.h>
#include <cuda_bf16.h>
#include <cuda_fp16.h>
#include <stdint.h>
#include <limits.h>

namespace {

constexpr int S_LEN = 2048;
constexpr int DM = 512;
constexpr int DH = 16;

__device__ __align__(128) __nv_bfloat16 g_Q[2][S_LEN][DM];
__device__ __align__(128) __nv_bfloat16 g_K[2][S_LEN][DH];
__device__ __align__(128) __nv_bfloat16 g_V[2][S_LEN][DH];
__device__ __align__(128) __nv_bfloat16 g_O[2][S_LEN][DM];
__device__ float g_gate[S_LEN];
__device__ uint32_t g_stat[2][32];

__device__ __forceinline__ uint32_t smem_u32(const void* p) { return (uint32_t)__cvta_generic_to_shared(p); }
__device__ __forceinline__ void cp_async16(uint32_t dst, const void* src) {
    asm volatile("cp.async.cg.shared.global [%0], [%1], 16;" ::"r"(dst), "l"(src));
}
__device__ __forceinline__ void cp_commit() { asm volatile("cp.async.commit_group;"); }
template <int N> __device__ __forceinline__ void cp_wait() { asm volatile("cp.async.wait_group %0;" ::"n"(N) : "memory"); }
__device__ __forceinline__ void fence_async_proxy() { asm volatile("fence.proxy.async.shared::cta;" ::: "memory"); }
__device__ __forceinline__ float bf16_round(float x) { return __bfloat162float(__float2bfloat16_rn(x)); }
__device__ __forceinline__ uint32_t pack_bf16(float lo, float hi) {
    uint32_t p;
    asm("cvt.rn.bf16x2.f32 %0, %1, %2;" : "=r"(p) : "f"(hi), "f"(lo));
    return p;
}
__device__ __forceinline__ float bf_lo(uint32_t v) { return __uint_as_float(v << 16); }
__device__ __forceinline__ float bf_hi(uint32_t v) { return __uint_as_float(v & 0xffff0000u); }
__device__ __forceinline__ uint32_t pack_f16(float lo, float hi) {
    uint32_t p;
    asm("cvt.rn.f16x2.f32 %0, %1, %2;" : "=r"(p) : "f"(hi), "f"(lo));
    return p;
}
__device__ __forceinline__ float2 unpack_f16(uint32_t v) { return __half22float2(*reinterpret_cast<__half2*>(&v)); }
__device__ __forceinline__ float rcp_approx(float x) { float r; asm("rcp.approx.ftz.f32 %0, %1;" : "=f"(r) : "f"(x)); return r; }
__device__ __forceinline__ float sqrt_approx(float x) { float r; asm("sqrt.approx.ftz.f32 %0, %1;" : "=f"(r) : "f"(x)); return r; }

#define WG_FENCE() asm volatile("wgmma.fence.sync.aligned;" ::: "memory")
#define WG_COMMIT() asm volatile("wgmma.commit_group.sync.aligned;" ::: "memory")
#define WG_WAIT(n) asm volatile("wgmma.wait_group.sync.aligned " #n ";" ::: "memory")
#define R8(b) "+f"(d[b + 0]), "+f"(d[b + 1]), "+f"(d[b + 2]), "+f"(d[b + 3]), "+f"(d[b + 4]), "+f"(d[b + 5]), "+f"(d[b + 6]), "+f"(d[b + 7])

__device__ __forceinline__ uint64_t mkdesc(uint32_t saddr, uint32_t sbo16, uint32_t lbo16 = 8) {
    uint32_t lo = ((saddr & 0x3FFFF) >> 4) | (lbo16 << 16);
    uint64_t d;
    asm("mov.b64 %0, {%1, %2};" : "=l"(d) : "r"(lo), "r"(sbo16));
    return d;
}
__device__ __forceinline__ uint64_t mkdesc_sw128(uint32_t saddr, uint32_t lbo16) {
    uint32_t lo = ((saddr & 0x3FFFF) >> 4) | (lbo16 << 16);
    uint64_t d;
    asm("mov.b64 %0, {%1, %2};" : "=l"(d) : "r"(lo), "r"(0x40000040u));
    return d;
}
template <int N> __device__ __forceinline__ void fence_regs(float* D) {
#pragma unroll
    for (int i = 0; i < N; i++) asm volatile("" : "+f"(D[i])::"memory");
}

__device__ __forceinline__ void wg_bf16_n64(float* d, uint64_t da, uint64_t db) {
    asm volatile(
        "wgmma.mma_async.sync.aligned.m64n64k16.f32.bf16.bf16 "
        "{%0,%1,%2,%3,%4,%5,%6,%7,%8,%9,%10,%11,%12,%13,%14,%15,%16,%17,%18,%19,%20,%21,%22,%23,%24,%25,%26,%27,%28,%29,%30,%31},"
        " %32, %33, 1, 1, 1, 0, 1;"
        : R8(0), R8(8), R8(16), R8(24)
        : "l"(da), "l"(db));
}
__device__ __forceinline__ void wg_bf16_n144(float* d, uint64_t da, uint64_t db) {
    asm volatile(
        "wgmma.mma_async.sync.aligned.m64n144k16.f32.bf16.bf16 "
        "{%0,%1,%2,%3,%4,%5,%6,%7,%8,%9,%10,%11,%12,%13,%14,%15,%16,%17,%18,%19,%20,%21,%22,%23,%24,%25,%26,%27,%28,%29,%30,%31,"
        "%32,%33,%34,%35,%36,%37,%38,%39,%40,%41,%42,%43,%44,%45,%46,%47,%48,%49,%50,%51,%52,%53,%54,%55,%56,%57,%58,%59,%60,%61,%62,%63,"
        "%64,%65,%66,%67,%68,%69,%70,%71}, %72, %73, 1, 1, 1, 0, 1;"
        : R8(0), R8(8), R8(16), R8(24), R8(32), R8(40), R8(48), R8(56), R8(64)
        : "l"(da), "l"(db));
}

constexpr int P_STAGES = 5;
constexpr int G_ABYTES = 128 * 128;
constexpr int G_BBLK = 64 * 128;
constexpr int P_STAGE = G_ABYTES + 3 * G_BBLK;
constexpr int P_SMEM = P_STAGES * P_STAGE;

__global__ void __launch_bounds__(256, 1) proj_kernel(const __nv_bfloat16* __restrict__ x,
                                                      const __nv_bfloat16* __restrict__ wqA, const __nv_bfloat16* __restrict__ wkA,
                                                      const __nv_bfloat16* __restrict__ wvA, const __nv_bfloat16* __restrict__ wqB,
                                                      const __nv_bfloat16* __restrict__ wkB, const __nv_bfloat16* __restrict__ wvB,
                                                      const __nv_bfloat16* __restrict__ gate_w) {
    extern __shared__ __align__(1024) unsigned char smem[];
    const int tid = threadIdx.x, warp = tid >> 5, lane = tid & 31, wg = tid >> 7;
    const int rb = blockIdx.x >> 3, cb = blockIdx.x & 7;
    const int br = cb >> 2;
    const __nv_bfloat16* Wq = (br ? wqB : wqA) + (cb & 3) * 128;
    const __nv_bfloat16* Wx = ((cb & 3) == 1) ? (br ? wvB : wvA) : (br ? wkB : wkA);
    const __nv_bfloat16* A = x + (size_t)rb * 128 * DM;
    const uint32_t sbase = smem_u32(smem);

    const int c8 = lane & 7, r4 = lane >> 3;
    auto load = [&](int chunk) {
        const uint32_t sa = sbase + (chunk % P_STAGES) * P_STAGE, sb = sa + G_ABYTES;
        const int k0 = chunk * 64;
#pragma unroll
        for (int i = 0; i < 4; i++) {
            const int r = warp * 16 + i * 4 + r4;
            cp_async16(sa + r * 128 + ((c8 ^ (r & 7)) << 4), A + (size_t)r * DM + k0 + c8 * 8);
        }
#pragma unroll
        for (int i = 0; i < 4; i++) {
            const int kr = warp * 8 + i * 2 + (lane >> 4), nb = (lane >> 3) & 1;
            cp_async16(sb + nb * G_BBLK + kr * 128 + ((c8 ^ (kr & 7)) << 4), Wq + (size_t)(k0 + kr) * DM + nb * 64 + c8 * 8);
        }
        if (lane < 16) {
            const int kr = warp * 8 + (lane >> 1), c = lane & 1;
            cp_async16(sb + 2 * G_BBLK + kr * 128 + ((c ^ (kr & 7)) << 4), Wx + (size_t)(k0 + kr) * DH + c * 8);
        }
        cp_commit();
    };
#pragma unroll
    for (int c = 0; c < P_STAGES; c++) load(c);

    {
        uint4 wv0 = *reinterpret_cast<const uint4*>(gate_w + lane * 8);
        uint4 wv1 = *reinterpret_cast<const uint4*>(gate_w + 256 + lane * 8);
        const uint32_t wp[8] = {wv0.x, wv0.y, wv0.z, wv0.w, wv1.x, wv1.y, wv1.z, wv1.w};
#pragma unroll
        for (int r = 0; r < 2; r++) {
            const int row = rb * 128 + cb * 16 + warp * 2 + r;
            uint4 x0 = *reinterpret_cast<const uint4*>(x + (size_t)row * DM + lane * 8);
            uint4 x1 = *reinterpret_cast<const uint4*>(x + (size_t)row * DM + 256 + lane * 8);
            const uint32_t xp[8] = {x0.x, x0.y, x0.z, x0.w, x1.x, x1.y, x1.z, x1.w};
            float s = 0.f;
#pragma unroll
            for (int j = 0; j < 8; j++) {
                s += bf16_round(bf_lo(xp[j]) * bf_lo(wp[j]));
                s += bf16_round(bf_hi(xp[j]) * bf_hi(wp[j]));
            }
#pragma unroll
            for (int o = 16; o > 0; o >>= 1) s += __shfl_xor_sync(0xffffffffu, s, o);
            if (lane == 0) g_gate[row] = bf16_round(1.f / (1.f + __expf(-bf16_round(s))));
        }
    }

    float acc[72];
#pragma unroll
    for (int i = 0; i < 72; i++) acc[i] = 0.f;
#pragma unroll
    for (int c = 0; c < 8; c++) {
        if (c == 0) cp_wait<P_STAGES - 1>(); else if (c == 1) cp_wait<P_STAGES - 2>(); else cp_wait<P_STAGES - 3>();
        fence_async_proxy();
        __syncthreads();
        if (c >= 2) { if (c - 2 + P_STAGES < 8) load(c - 2 + P_STAGES); else cp_commit(); }
        const uint32_t sa = sbase + (c % P_STAGES) * P_STAGE + wg * 8192, sb = sbase + (c % P_STAGES) * P_STAGE + G_ABYTES;
        WG_FENCE();
#pragma unroll
        for (int kk = 0; kk < 4; kk++) wg_bf16_n144(acc, mkdesc_sw128(sa + kk * 32, 1), mkdesc_sw128(sb + kk * 2048, G_BBLK / 16));
        WG_COMMIT();
        WG_WAIT(1);
    }
    WG_WAIT(0);
    fence_regs<72>(acc);

    const int g = lane >> 2, t = lane & 3;
    const int row0 = rb * 128 + wg * 64 + (warp & 3) * 16 + g;
#pragma unroll
    for (int h = 0; h < 8; h++) {
        uint2 a, b;
        a.x = pack_bf16(acc[8 * h + 0], acc[8 * h + 1]); a.y = pack_bf16(acc[8 * h + 4], acc[8 * h + 5]);
        b.x = pack_bf16(acc[8 * h + 2], acc[8 * h + 3]); b.y = pack_bf16(acc[8 * h + 6], acc[8 * h + 7]);
        *reinterpret_cast<uint2*>(&g_Q[br][row0][(cb & 3) * 128 + h * 16 + t * 4]) = a;
        *reinterpret_cast<uint2*>(&g_Q[br][row0 + 8][(cb & 3) * 128 + h * 16 + t * 4]) = b;
    }
    if ((cb & 3) < 2) {
        uint32_t p0 = pack_bf16(acc[64], acc[65]), p1 = pack_bf16(acc[66], acc[67]);
        uint32_t p2 = pack_bf16(acc[68], acc[69]), p3 = pack_bf16(acc[70], acc[71]);
        __nv_bfloat16* dst = (cb & 3) ? &g_V[br][0][0] : &g_K[br][0][0];
        *reinterpret_cast<uint32_t*>(dst + row0 * DH + 2 * t) = p0;
        *reinterpret_cast<uint32_t*>(dst + row0 * DH + 8 + 2 * t) = p2;
        *reinterpret_cast<uint32_t*>(dst + (row0 + 8) * DH + 2 * t) = p1;
        *reinterpret_cast<uint32_t*>(dst + (row0 + 8) * DH + 8 + 2 * t) = p3;
        if ((cb & 3) == 0) {
            float n0 = bf_lo(p0) * bf_lo(p0) + bf_hi(p0) * bf_hi(p0) + bf_lo(p2) * bf_lo(p2) + bf_hi(p2) * bf_hi(p2);
            float n1 = bf_lo(p1) * bf_lo(p1) + bf_hi(p1) * bf_hi(p1) + bf_lo(p3) * bf_lo(p3) + bf_hi(p3) * bf_hi(p3);
            n0 += __shfl_xor_sync(0xffffffffu, n0, 1); n0 += __shfl_xor_sync(0xffffffffu, n0, 2);
            n1 += __shfl_xor_sync(0xffffffffu, n1, 1); n1 += __shfl_xor_sync(0xffffffffu, n1, 2);
            if (!(n0 <= 3.0e38f)) n0 = 3.0e38f;
            if (!(n1 <= 3.0e38f)) n1 = 3.0e38f;
            float n = fmaxf(n0, n1);
#pragma unroll
            for (int o = 4; o < 32; o <<= 1) n = fmaxf(n, __shfl_xor_sync(0xffffffffu, n, o));
            if (lane == 0) atomicMax(&g_stat[br][0], __float_as_uint(n));
        } else {
            float v[4] = {fmaxf(fabsf(bf_lo(p0)), fabsf(bf_lo(p1))), fmaxf(fabsf(bf_hi(p0)), fabsf(bf_hi(p1))),
                          fmaxf(fabsf(bf_lo(p2)), fabsf(bf_lo(p3))), fmaxf(fabsf(bf_hi(p2)), fabsf(bf_hi(p3)))};
#pragma unroll
            for (int o = 4; o < 32; o <<= 1)
#pragma unroll
                for (int i = 0; i < 4; i++) v[i] = fmaxf(v[i], __shfl_xor_sync(0xffffffffu, v[i], o));
            if (lane < 4) {
                atomicMax(&g_stat[br][1 + 2 * t], __float_as_uint(v[0]));
                atomicMax(&g_stat[br][2 + 2 * t], __float_as_uint(v[1]));
                atomicMax(&g_stat[br][9 + 2 * t], __float_as_uint(v[2]));
                atomicMax(&g_stat[br][10 + 2 * t], __float_as_uint(v[3]));
            }
        }
    }
}

constexpr int O_STAGES = 8;
constexpr int O_STAGE = G_ABYTES + G_BBLK;
constexpr int O_SMEM = O_STAGES * O_STAGE;

__global__ void __launch_bounds__(256, 1) out_kernel(const __nv_bfloat16* __restrict__ woA, const __nv_bfloat16* __restrict__ woB,
                                                     __nv_bfloat16* __restrict__ out) {
    extern __shared__ __align__(1024) unsigned char smem[];
    const int tid = threadIdx.x, warp = tid >> 5, lane = tid & 31, wg = tid >> 7;
    const int rb = blockIdx.x >> 3, cb = blockIdx.x & 7;
    const uint32_t sbase = smem_u32(smem);
    const int c8 = lane & 7, r4 = lane >> 3;
    auto load = [&](int chunk) {
        const uint32_t sa = sbase + (chunk % O_STAGES) * O_STAGE, sb = sa + G_ABYTES;
        const int b = chunk >> 3, k0 = (chunk & 7) * 64;
        const __nv_bfloat16* A = &g_O[b][rb * 128][0];
        const __nv_bfloat16* W = (b ? woB : woA) + cb * 64;
#pragma unroll
        for (int i = 0; i < 4; i++) {
            const int r = warp * 16 + i * 4 + r4;
            cp_async16(sa + r * 128 + ((c8 ^ (r & 7)) << 4), A + (size_t)r * DM + k0 + c8 * 8);
        }
#pragma unroll
        for (int i = 0; i < 2; i++) {
            const int kr = warp * 8 + i * 4 + r4;
            cp_async16(sb + kr * 128 + ((c8 ^ (kr & 7)) << 4), W + (size_t)(k0 + kr) * DM + c8 * 8);
        }
        cp_commit();
    };
#pragma unroll
    for (int c = 0; c < O_STAGES; c++) load(c);
    if (blockIdx.x == 0 && tid < 64) (&g_stat[0][0])[tid] = 0u;

    float accA[32], accB[32];
#pragma unroll
    for (int i = 0; i < 32; i++) { accA[i] = 0.f; accB[i] = 0.f; }
#pragma unroll
    for (int c = 0; c < 16; c++) {
        if (c == 0) cp_wait<O_STAGES - 1>(); else if (c == 1) cp_wait<O_STAGES - 2>(); else cp_wait<O_STAGES - 3>();
        fence_async_proxy();
        __syncthreads();
        if (c >= 2) { if (c - 2 + O_STAGES < 16) load(c - 2 + O_STAGES); else cp_commit(); }
        const uint32_t sa = sbase + (c % O_STAGES) * O_STAGE + wg * 8192, sb = sbase + (c % O_STAGES) * O_STAGE + G_ABYTES;
        WG_FENCE();
#pragma unroll
        for (int kk = 0; kk < 4; kk++) wg_bf16_n64(c < 8 ? accA : accB, mkdesc_sw128(sa + kk * 32, 1), mkdesc_sw128(sb + kk * 2048, G_BBLK / 16));
        WG_COMMIT();
        WG_WAIT(1);
    }
    WG_WAIT(0);
    fence_regs<32>(accA);
    fence_regs<32>(accB);

    const int g = lane >> 2, t = lane & 3;
#pragma unroll
    for (int h = 0; h < 2; h++) {
        const int row = rb * 128 + wg * 64 + (warp & 3) * 16 + g + h * 8;
        const float gt = g_gate[row];
        const float og = bf16_round(1.f - gt);
#pragma unroll
        for (int j = 0; j < 8; j++) {
            float r0 = bf16_round(gt * bf16_round(accA[4 * j + 2 * h])) + bf16_round(og * bf16_round(accB[4 * j + 2 * h]));
            float r1 = bf16_round(gt * bf16_round(accA[4 * j + 2 * h + 1])) + bf16_round(og * bf16_round(accB[4 * j + 2 * h + 1]));
            *reinterpret_cast<uint32_t*>(out + (size_t)row * DM + cb * 64 + j * 8 + t * 2) = pack_bf16(r0, r1);
        }
    }
}

#define ATT_POLY 1
#define ATT_MASK 0x9248
constexpr int A_NT = 128;
constexpr int A_NTH = 256;
constexpr uint32_t A_MASK = ATT_MASK;
constexpr float A_OFFP = (ATT_POLY == 1) ? 29.75f : 28.75f;
constexpr float A_LK = (ATT_POLY == 1) ? 0.59368f : 1.71838f;
constexpr float A_WIN = A_OFFP - 0.15f;
constexpr int A_FL = 4;
constexpr float A_VS = 1.f / 512.f;
constexpr uint32_t A_ONES = 0x18001800u;
constexpr float A_LMIN = 0.0625f;
constexpr float A_C = 0.25f * 1.4426950408889634f;

constexpr int SM_K = 0;
constexpr int SM_V = 65536;
constexpr int SM_Q = SM_V + 98304;
constexpr int SM_M = SM_Q + 32768;
constexpr int SM_L = SM_M + 4096;
constexpr int SM_TOTAL = SM_L + 16 + 2048 + 8192;

__device__ __forceinline__ void bump(uint64_t& d, uint32_t inc16) {
    asm volatile("{.reg .b32 lo, hi; mov.b64 {lo, hi}, %0; add.u32 lo, lo, %1; mov.b64 %0, {lo, hi};}" : "+l"(d) : "r"(inc16));
}
__device__ __forceinline__ void wg_qk128(float* d, const uint32_t* a, uint64_t desc) {
    asm volatile(
        "wgmma.mma_async.sync.aligned.m64n128k16.f32.f16.f16 "
        "{%0,%1,%2,%3,%4,%5,%6,%7,%8,%9,%10,%11,%12,%13,%14,%15,%16,%17,%18,%19,%20,%21,%22,%23,%24,%25,%26,%27,%28,%29,%30,%31,"
        "%32,%33,%34,%35,%36,%37,%38,%39,%40,%41,%42,%43,%44,%45,%46,%47,%48,%49,%50,%51,%52,%53,%54,%55,%56,%57,%58,%59,%60,%61,%62,%63},"
        " {%64,%65,%66,%67}, %68, 1, 1, 1, 0;"
        : R8(0), R8(8), R8(16), R8(24), R8(32), R8(40), R8(48), R8(56)
        : "r"(a[0]), "r"(a[1]), "r"(a[2]), "r"(a[3]), "l"(desc));
}
__device__ __forceinline__ void wg_pv24h(uint32_t* d, const uint32_t* a, uint64_t desc) {
    asm volatile(
        "wgmma.mma_async.sync.aligned.m64n24k16.f16.f16.f16 {%0,%1,%2,%3,%4,%5}, {%6,%7,%8,%9}, %10, 1, 1, 1, 1;"
        : "+r"(d[0]), "+r"(d[1]), "+r"(d[2]), "+r"(d[3]), "+r"(d[4]), "+r"(d[5])
        : "r"(a[0]), "r"(a[1]), "r"(a[2]), "r"(a[3]), "l"(desc));
}
__device__ __forceinline__ uint32_t poly_pair(float y0, float y1) {
    uint32_t z, w, t;
    asm("prmt.b32 %0, %1, %2, 0x6521;" : "=r"(z) : "f"(y0), "f"(y1));
    asm("lop3.b32 %0, %1, 0x03ff03ff, 0x38003800, 0xEA;" : "=r"(w) : "r"(z));
    asm("fma.rn.f16x2 %0, %1, %1, %2;" : "=r"(t) : "r"(w), "r"(0x380b380b));
    return z + t - w;
}
__device__ __forceinline__ uint32_t mufu_pair(float x0, float x1) {
    float a, b;
    asm("ex2.approx.ftz.f32 %0, %1;" : "=f"(a) : "f"(x0));
    asm("ex2.approx.ftz.f32 %0, %1;" : "=f"(b) : "f"(x1));
    return pack_f16(a, b);
}
template <int J0, int J1>
__device__ __forceinline__ void exp_block(const float* D, uint32_t* P) {
#pragma unroll
    for (int j = J0; j < J1; j++) {
        if ((A_MASK >> j) & 1) {
            P[2 * (j - J0)] = mufu_pair(D[4 * j], D[4 * j + 1]);
            P[2 * (j - J0) + 1] = mufu_pair(D[4 * j + 2], D[4 * j + 3]);
        } else {
            P[2 * (j - J0)] = poly_pair(D[4 * j], D[4 * j + 1]);
            P[2 * (j - J0) + 1] = poly_pair(D[4 * j + 2], D[4 * j + 3]);
        }
    }
}

__device__ __forceinline__ float pow2_norm(uint32_t vbits) {
    int e = (int)((vbits >> 23) & 0xff);
    e = min(max(e, 1), 250);
    return __uint_as_float((uint32_t)(253 - e) << 23);
}
__device__ __forceinline__ float pow2_inv(float p) { return __uint_as_float(0x7f000000u - __float_as_uint(p)); }

__device__ __forceinline__ void load_q_row(float* q, int br, int row, int head) {
    const __nv_bfloat16* qp = &g_Q[br][row][head * DH];
#pragma unroll
    for (int t = 0; t < 4; t++) {
        q[2 * t] = __bfloat162float(qp[4 * t]) * A_C;
        q[2 * t + 1] = __bfloat162float(qp[4 * t + 1]) * A_C;
        q[8 + 2 * t] = __bfloat162float(qp[4 * t + 2]) * A_C;
        q[9 + 2 * t] = __bfloat162float(qp[4 * t + 3]) * A_C;
    }
}
__device__ __forceinline__ float dot_key(const float* q, int br, int j) {
    uint4 k0 = *reinterpret_cast<const uint4*>(&g_K[br][j][0]);
    uint4 k1 = *reinterpret_cast<const uint4*>(&g_K[br][j][8]);
    const uint32_t kk[8] = {k0.x, k0.y, k0.z, k0.w, k1.x, k1.y, k1.z, k1.w};
    float s = 0.f;
#pragma unroll
    for (int d = 0; d < 8; d++) s += q[2 * d] * bf_lo(kk[d]) + q[2 * d + 1] * bf_hi(kk[d]);
    return s;
}

__device__ __noinline__ void attn_safe_row(int br, int row, int head, int t4, unsigned qmask) {
    float q[DH], o[DH];
    load_q_row(q, br, row, head);
#pragma unroll
    for (int d = 0; d < DH; d++) o[d] = 0.f;
    float m = -INFINITY, l = 0.f;
    for (int j = t4; j < S_LEN; j += 4) {
        float s = dot_key(q, br, j);
        uint4 v0 = *reinterpret_cast<const uint4*>(&g_V[br][j][0]);
        uint4 v1 = *reinterpret_cast<const uint4*>(&g_V[br][j][8]);
        const uint32_t vv[8] = {v0.x, v0.y, v0.z, v0.w, v1.x, v1.y, v1.z, v1.w};
        float mn = fmaxf(m, s);
        float c = exp2f(m - mn), p = exp2f(s - mn);
        if (mn == -INFINITY) { c = 1.f; p = 0.f; }
        l = l * c + p;
#pragma unroll
        for (int d = 0; d < 8; d++) {
            o[2 * d] = o[2 * d] * c + p * bf_lo(vv[d]);
            o[2 * d + 1] = o[2 * d + 1] * c + p * bf_hi(vv[d]);
        }
        m = mn;
    }
    float mm = fmaxf(m, __shfl_xor_sync(qmask, m, 1));
    mm = fmaxf(mm, __shfl_xor_sync(qmask, mm, 2));
    float c = (mm == -INFINITY) ? 1.f : exp2f(m - mm);
    l *= c;
    l += __shfl_xor_sync(qmask, l, 1);
    l += __shfl_xor_sync(qmask, l, 2);
    float inv = 1.f / l;
    __nv_bfloat16* op = &g_O[br][row][head * DH];
#pragma unroll
    for (int d = 0; d < DH; d++) {
        float v = o[d] * c;
        v += __shfl_xor_sync(qmask, v, 1);
        v += __shfl_xor_sync(qmask, v, 2);
        if ((d >> 2) == t4) op[d] = __float2bfloat16_rn(v * inv);
    }
}

__device__ __forceinline__ void flush_acc(float* O, uint32_t* H) {
#pragma unroll
    for (int i = 0; i < 6; i++) asm volatile("" : "+r"(H[i])::"memory");
#pragma unroll
    for (int i = 0; i < 4; i++) { float2 f = unpack_f16(H[i]); O[2 * i] += f.x; O[2 * i + 1] += f.y; }
    O[8] += unpack_f16(H[4]).x;
    O[9] += unpack_f16(H[5]).x;
#pragma unroll
    for (int i = 0; i < 6; i++) H[i] = 0u;
}

__device__ __forceinline__ void attn_loop(float* DA, float* DB, float* OA, float* OB, const uint32_t* qA, const uint32_t* qB,
                                          uint32_t sK, uint32_t sV) {
    uint32_t P0[16], P1[16];
    uint32_t HA[6] = {0u, 0u, 0u, 0u, 0u, 0u}, HB[6] = {0u, 0u, 0u, 0u, 0u, 0u};
    uint64_t dkA = mkdesc(sK, 16), dkB = mkdesc(sK, 16);
    uint64_t dv[8];
#pragma unroll
    for (int j = 0; j < 8; j++) dv[j] = mkdesc(sV + j * 768, 16);
    WG_FENCE();
    wg_qk128(DA, qA, dkA);
    WG_COMMIT();
    WG_WAIT(0);
    fence_regs<64>(DA);
#pragma unroll 1
    for (int grp = 0; grp < S_LEN / A_NT / A_FL; grp++) {
#pragma unroll 1
        for (int t = 0; t < A_FL; t++) {
            WG_FENCE();
            wg_qk128(DB, qB, dkB);
            WG_COMMIT();
            bump(dkB, A_NT * 2);
            bump(dkA, A_NT * 2);
            exp_block<0, 8>(DA, P0);
            WG_FENCE();
#pragma unroll
            for (int j = 0; j < 4; j++) wg_pv24h(HA, &P0[4 * j], dv[j]);
            WG_COMMIT();
            WG_WAIT(2);
            exp_block<8, 16>(DA, P1);
            WG_FENCE();
#pragma unroll
            for (int j = 4; j < 8; j++) wg_pv24h(HA, &P1[4 * (j - 4)], dv[j]);
            WG_COMMIT();
            WG_WAIT(1);
            fence_regs<64>(DB);
            WG_FENCE();
            wg_qk128(DA, qA, dkA);
            WG_COMMIT();
            exp_block<0, 8>(DB, P0);
            WG_FENCE();
#pragma unroll
            for (int j = 0; j < 4; j++) { wg_pv24h(HB, &P0[4 * j], dv[j]); bump(dv[j], A_NT * 3); }
            WG_COMMIT();
            WG_WAIT(2);
            exp_block<8, 16>(DB, P1);
            WG_FENCE();
#pragma unroll
            for (int j = 4; j < 8; j++) { wg_pv24h(HB, &P1[4 * (j - 4)], dv[j]); bump(dv[j], A_NT * 3); }
            WG_COMMIT();
            WG_WAIT(1);
            fence_regs<64>(DA);
        }
        WG_WAIT(0);
        flush_acc(OA, HA);
        flush_acc(OB, HB);
    }
}

struct RowPrep { uint32_t qf[4]; float m0, m1; };

__device__ __forceinline__ void prep_rows(RowPrep& r, const unsigned char* sq, float cq, float kmaxn) {
    uint2 ra = *reinterpret_cast<const uint2*>(sq);
    uint2 rc = *reinterpret_cast<const uint2*>(sq + 8 * 256);
    r.qf[0] = pack_f16(bf_lo(ra.x) * cq, bf_hi(ra.x) * cq);
    r.qf[1] = pack_f16(bf_lo(rc.x) * cq, bf_hi(rc.x) * cq);
    r.qf[2] = pack_f16(bf_lo(ra.y) * cq, bf_hi(ra.y) * cq);
    r.qf[3] = pack_f16(bf_lo(rc.y) * cq, bf_hi(rc.y) * cq);
    float2 a = unpack_f16(r.qf[0]), b = unpack_f16(r.qf[2]), c = unpack_f16(r.qf[1]), d = unpack_f16(r.qf[3]);
    float n0 = a.x * a.x + a.y * a.y + b.x * b.x + b.y * b.y;
    float n1 = c.x * c.x + c.y * c.y + d.x * d.x + d.y * d.y;
    n0 += __shfl_xor_sync(0xffffffffu, n0, 1); n0 += __shfl_xor_sync(0xffffffffu, n0, 2);
    n1 += __shfl_xor_sync(0xffffffffu, n1, 1); n1 += __shfl_xor_sync(0xffffffffu, n1, 2);
    r.m0 = sqrt_approx(n0) * kmaxn + 0.01f;
    r.m1 = sqrt_approx(n1) * kmaxn + 0.01f;
}
__device__ __forceinline__ int f2ord(float f) { int i = __float_as_int(f); return i ^ ((i >> 31) & 0x7fffffff); }
__device__ __forceinline__ float ord2f(int i) { return __int_as_float(i ^ ((i >> 31) & 0x7fffffff)); }
__device__ __forceinline__ void init_acc(float* D, float* O, float m0, float m1) {
    if (!(m0 == m0)) m0 = 0.f;
    if (!(m1 == m1)) m1 = 0.f;
    const float cp0 = 2.f + (A_OFFP - m0) * 0.0625f + 3.0517578125e-5f, cp1 = 2.f + (A_OFFP - m1) * 0.0625f + 3.0517578125e-5f;
    const float cm0 = A_OFFP - 15.f + A_LK - m0, cm1 = A_OFFP - 15.f + A_LK - m1;
#pragma unroll
    for (int j = 0; j < 16; j++) {
        const bool mu = (A_MASK >> j) & 1;
        D[4 * j] = D[4 * j + 1] = mu ? cm0 : cp0;
        D[4 * j + 2] = D[4 * j + 3] = mu ? cm1 : cp1;
    }
#pragma unroll
    for (int i = 0; i < 10; i++) O[i] = 0.f;
}
__device__ __forceinline__ uint32_t finish_rows(const float* O, float m0, float m1, int br, int row0, int head, int lane) {
    const int t4 = lane & 3;
    const bool bad0 = !(m0 == m0) || !(O[8] >= A_LMIN && O[8] < 1e30f);
    const bool bad1 = !(m1 == m1) || !(O[9] >= A_LMIN && O[9] < 1e30f);
    float ib[4];
#pragma unroll
    for (int i = 0; i < 4; i++) ib[i] = pow2_inv(pow2_norm(g_stat[br][1 + t4 * 4 + i]));
    const float i0 = __frcp_rn(O[8]), i1 = __frcp_rn(O[9]);
    uint2 a, b;
    a.x = pack_bf16(O[0] * i0 * ib[0], O[1] * i0 * ib[1]);
    a.y = pack_bf16(O[4] * i0 * ib[2], O[5] * i0 * ib[3]);
    b.x = pack_bf16(O[2] * i1 * ib[0], O[3] * i1 * ib[1]);
    b.y = pack_bf16(O[6] * i1 * ib[2], O[7] * i1 * ib[3]);
    if (!bad0) *reinterpret_cast<uint2*>(&g_O[br][row0][head * DH + t4 * 4]) = a;
    if (!bad1) *reinterpret_cast<uint2*>(&g_O[br][row0 + 8][head * DH + t4 * 4]) = b;
    return (bad0 ? 1u : 0u) | (bad1 ? 2u : 0u);
}

__global__ void __launch_bounds__(A_NTH, 1) attn_kernel() {
    extern __shared__ __align__(1024) unsigned char smem[];
    const int tid = threadIdx.x, lane = tid & 31;
    const int wg = tid >> 7, warp_in_wg = (tid >> 5) & 3;
    const int br = blockIdx.x >> 6;
    const int qb = (blockIdx.x >> 2) & 15;
    const int hg = blockIdx.x & 3;

    int* l_cnt = reinterpret_cast<int*>(smem + SM_L);
    unsigned short* l_id = reinterpret_cast<unsigned short*>(smem + SM_L + 16);
    int* l_mx = reinterpret_cast<int*>(smem + SM_L + 16 + 2048);
    int* l_mn = l_mx + 1024;
    if (tid == 0) *l_cnt = 0;
    {
        const uint32_t sq = smem_u32(smem + SM_Q);
#pragma unroll
        for (int i = 0; i < 8; i++) {
            const int c = tid + i * 256, r = c >> 4, ch = c & 15;
            cp_async16(sq + r * 256 + ch * 16, &g_Q[br][qb * 128 + r][hg * 128 + ch * 8]);
        }
        cp_commit();
    }
    const float kmax = sqrt_approx(__uint_as_float(g_stat[br][0]));
    const float alpha = pow2_norm(__float_as_uint(kmax));
    const float kmaxn = kmax * alpha * 16.04f;

    {
        const int c = tid >> 1, hf = tid & 1;
        float beta[8];
#pragma unroll
        for (int i = 0; i < 8; i++) beta[i] = pow2_norm(g_stat[br][1 + hf * 8 + i]) * A_VS;
        const float ksc = ((A_MASK >> (c >> 3)) & 1) ? alpha * 16.f : alpha;
        float acc[8];
#pragma unroll
        for (int i = 0; i < 8; i++) acc[i] = 0.f;
        unsigned char* kdst = smem + SM_K + (c >> 3) * 256 + hf * 128 + (c & 7) * 16;
        unsigned char* vdst = smem + SM_V + (c >> 4) * 768 + ((c >> 3) & 1) * 128 + (c & 7) * 16 + hf * 8;
#pragma unroll
        for (int tb = 0; tb < 2; tb++) {
            uint4 kr[8], vr[8];
#pragma unroll
            for (int i = 0; i < 8; i++) {
                const int key = (tb * 8 + i) * A_NT + c;
                kr[i] = *reinterpret_cast<const uint4*>(&g_K[br][key][hf * 8]);
                vr[i] = *reinterpret_cast<const uint4*>(&g_V[br][key][hf * 8]);
            }
#pragma unroll
            for (int i = 0; i < 8; i++) {
                const int t = tb * 8 + i;
                const uint32_t kk[4] = {kr[i].x, kr[i].y, kr[i].z, kr[i].w};
                uint32_t dd[4];
#pragma unroll
                for (int j = 0; j < 4; j++) {
                    dd[j] = pack_f16(bf_lo(kk[j]) * ksc - acc[2 * j], bf_hi(kk[j]) * ksc - acc[2 * j + 1]);
                    float2 f = unpack_f16(dd[j]);
                    acc[2 * j] += f.x; acc[2 * j + 1] += f.y;
                }
                *reinterpret_cast<uint4*>(kdst + t * (A_NT * 32)) = make_uint4(dd[0], dd[1], dd[2], dd[3]);
                uint32_t v0 = pack_f16(bf_lo(vr[i].x) * beta[0], bf_hi(vr[i].x) * beta[1]);
                uint32_t v1 = pack_f16(bf_lo(vr[i].y) * beta[2], bf_hi(vr[i].y) * beta[3]);
                uint32_t v2 = pack_f16(bf_lo(vr[i].z) * beta[4], bf_hi(vr[i].z) * beta[5]);
                uint32_t v3 = pack_f16(bf_lo(vr[i].w) * beta[6], bf_hi(vr[i].w) * beta[7]);
                unsigned char* vb = vdst + t * (A_NT * 48);
                *reinterpret_cast<uint2*>(vb) = make_uint2(v0, v2);
                *reinterpret_cast<uint2*>(vb + 256) = make_uint2(v1, v3);
                *reinterpret_cast<uint2*>(vb + 512) = make_uint2(A_ONES, A_ONES);
            }
        }
    }
    cp_wait<0>();
    fence_async_proxy();
    __syncthreads();

    const int g = lane >> 2, t4 = lane & 3;
    const int rloc = wg * 64 + warp_in_wg * 16 + g;
    const int row0 = qb * 128 + rloc;
    const float cq = (A_C / 16.f) * pow2_inv(alpha);
    const uint32_t sK = smem_u32(smem + SM_K), sV = smem_u32(smem + SM_V);

    float* sm_m = reinterpret_cast<float*>(smem + SM_M);
#pragma unroll 2
    for (int h = 0; h < 8; h++) {
        unsigned char* sq = smem + SM_Q + rloc * 256 + h * 32 + t4 * 8;
        RowPrep r;
        prep_rows(r, sq, cq, kmaxn);
        *reinterpret_cast<uint2*>(sq) = make_uint2(r.qf[0], r.qf[2]);
        *reinterpret_cast<uint2*>(sq + 8 * 256) = make_uint2(r.qf[1], r.qf[3]);
        if (t4 == 0) {
            sm_m[h * 128 + rloc] = r.m0;
            sm_m[h * 128 + rloc + 8] = r.m1;
            if (!(2.f * r.m0 <= A_WIN)) { int e = atomicAdd(l_cnt, 1); l_id[e] = (unsigned short)(h * 128 + rloc); l_mx[e] = INT_MIN; l_mn[e] = INT_MAX; }
            if (!(2.f * r.m1 <= A_WIN)) { int e = atomicAdd(l_cnt, 1); l_id[e] = (unsigned short)(h * 128 + rloc + 8); l_mx[e] = INT_MIN; l_mn[e] = INT_MAX; }
        }
    }
    __syncthreads();
    const int n_list = *l_cnt;
    if (n_list > 0) {
        uint4 kr[16];
#pragma unroll
        for (int i = 0; i < 8; i++) {
            kr[2 * i] = *reinterpret_cast<const uint4*>(&g_K[br][tid + i * 256][0]);
            kr[2 * i + 1] = *reinterpret_cast<const uint4*>(&g_K[br][tid + i * 256][8]);
        }
        const float ssc = 16.f * alpha;
#pragma unroll 1
        for (int e = 0; e < n_list; e++) {
            const int id = l_id[e];
            const uint4* qp = reinterpret_cast<const uint4*>(smem + SM_Q + (id & 127) * 256 + (id >> 7) * 32);
            const uint4 qa = qp[0], qc = qp[1];
            const float2 q0 = unpack_f16(qa.x), q4 = unpack_f16(qa.y), q1 = unpack_f16(qa.z), q5 = unpack_f16(qa.w);
            const float2 q2 = unpack_f16(qc.x), q6 = unpack_f16(qc.y), q3 = unpack_f16(qc.z), q7 = unpack_f16(qc.w);
            float mx = -INFINITY, mn = INFINITY;
#pragma unroll
            for (int i = 0; i < 8; i++) {
                const uint4 a = kr[2 * i], b = kr[2 * i + 1];
                float sc = q0.x * bf_lo(a.x) + q0.y * bf_hi(a.x) + q1.x * bf_lo(a.y) + q1.y * bf_hi(a.y) + q2.x * bf_lo(a.z) + q2.y * bf_hi(a.z) +
                           q3.x * bf_lo(a.w) + q3.y * bf_hi(a.w) + q4.x * bf_lo(b.x) + q4.y * bf_hi(b.x) + q5.x * bf_lo(b.y) + q5.y * bf_hi(b.y) +
                           q6.x * bf_lo(b.z) + q6.y * bf_hi(b.z) + q7.x * bf_lo(b.w) + q7.y * bf_hi(b.w);
                sc *= ssc;
                if (!(sc == sc)) sc = INFINITY;
                mx = fmaxf(mx, sc);
                mn = fminf(mn, sc);
            }
#pragma unroll
            for (int o = 16; o > 0; o >>= 1) {
                mx = fmaxf(mx, __shfl_xor_sync(0xffffffffu, mx, o));
                mn = fminf(mn, __shfl_xor_sync(0xffffffffu, mn, o));
            }
            if (lane == 0) { atomicMax(&l_mx[e], f2ord(mx)); atomicMin(&l_mn[e], f2ord(mn)); }
        }
        __syncthreads();
        for (int e = tid; e < n_list; e += A_NTH) {
            const int id = l_id[e];
            const float bnd = sm_m[id];
            const float slack = 0.02f + bnd * 0.001f;
            float m = ord2f(l_mx[e]) + slack;
            if (!(m - (ord2f(l_mn[e]) - slack) <= A_WIN) || !(bnd < 1.0e4f)) m = __int_as_float(0x7fc00000);
            sm_m[id] = m;
        }
        __syncthreads();
    }

    uint32_t badmask = 0;
#pragma unroll 1
    for (int hp = 0; hp < 4; hp++) {
        const int head = hg * 8 + hp * 2;
        const unsigned char* sq = smem + SM_Q + rloc * 256 + hp * 64 + t4 * 8;
        uint32_t qA[4], qB[4];
        {
            uint2 a0 = *reinterpret_cast<const uint2*>(sq), a1 = *reinterpret_cast<const uint2*>(sq + 8 * 256);
            uint2 b0 = *reinterpret_cast<const uint2*>(sq + 32), b1 = *reinterpret_cast<const uint2*>(sq + 32 + 8 * 256);
            qA[0] = a0.x; qA[1] = a1.x; qA[2] = a0.y; qA[3] = a1.y;
            qB[0] = b0.x; qB[1] = b1.x; qB[2] = b0.y; qB[3] = b1.y;
        }
        const float* mp = sm_m + hp * 256 + rloc;
        float DA[64], DB[64], OA[10], OB[10];
        init_acc(DA, OA, mp[0], mp[8]);
        init_acc(DB, OB, mp[128], mp[136]);
        attn_loop(DA, DB, OA, OB, qA, qB, sK, sV);
        badmask |= finish_rows(OA, mp[0], mp[8], br, row0, head, lane) << (hp * 4);
        badmask |= finish_rows(OB, mp[128], mp[136], br, row0, head + 1, lane) << (hp * 4 + 2);
    }
    const unsigned qmask = 0xFu << (lane & 28);
    while (badmask) {
        const int b = __ffs(badmask) - 1;
        attn_safe_row(br, row0 + (b & 1) * 8, hg * 8 + (b >> 1), t4, qmask);
        badmask &= badmask - 1;
    }
}

}

extern "C" void kernel_launch(void* const* d_in, const int* in_sizes, int n_in, void* d_out, int out_size) {
    const __nv_bfloat16* x = (const __nv_bfloat16*)d_in[0];
    const __nv_bfloat16* wqA = (const __nv_bfloat16*)d_in[1];
    const __nv_bfloat16* wkA = (const __nv_bfloat16*)d_in[2];
    const __nv_bfloat16* wvA = (const __nv_bfloat16*)d_in[3];
    const __nv_bfloat16* woA = (const __nv_bfloat16*)d_in[4];
    const __nv_bfloat16* wqB = (const __nv_bfloat16*)d_in[6];
    const __nv_bfloat16* wkB = (const __nv_bfloat16*)d_in[7];
    const __nv_bfloat16* wvB = (const __nv_bfloat16*)d_in[8];
    const __nv_bfloat16* woB = (const __nv_bfloat16*)d_in[9];
    const __nv_bfloat16* gw = (const __nv_bfloat16*)d_in[10];
    __nv_bfloat16* out = (__nv_bfloat16*)d_out;

    static bool attr_set = false;
    if (!attr_set) {
        cudaFuncSetAttribute(proj_kernel, cudaFuncAttributeMaxDynamicSharedMemorySize, P_SMEM);
        cudaFuncSetAttribute(attn_kernel, cudaFuncAttributeMaxDynamicSharedMemorySize, SM_TOTAL);
        cudaFuncSetAttribute(out_kernel, cudaFuncAttributeMaxDynamicSharedMemorySize, O_SMEM);
        attr_set = true;
    }
    proj_kernel<<<128, 256, P_SMEM>>>(x, wqA, wkA, wvA, wqB, wkB, wvB, gw);
    attn_kernel<<<128, A_NTH, SM_TOTAL>>>();
    out_kernel<<<128, 256, O_SMEM>>>(woA, woB, out);
}
```

```cpp
#include <cuda_runtime.h>
#include <cuda_bf16.h>
#include <cuda_fp16.h>
#include <stdint.h>
#include <limits.h>

namespace {

constexpr int S_LEN = 2048;
constexpr int DM = 512;
constexpr int DH = 16;

__device__ __align__(128) __nv_bfloat16 g_Q[2][S_LEN][DM];
__device__ __align__(128) __nv_bfloat16 g_K[2][S_LEN][DH];
__device__ __align__(128) __nv_bfloat16 g_V[2][S_LEN][DH];
__device__ __align__(128) __nv_bfloat16 g_O[2][S_LEN][DM];
__device__ float g_gate[S_LEN];
__device__ uint32_t g_stat[2][2][32];
__device__ unsigned int g_bar[2][32];
__device__ unsigned int g_flag[16][8];

#define TL(k, i)
__device__ __forceinline__ uint32_t smem_u32(const void* p) { return (uint32_t)__cvta_generic_to_shared(p); }
__device__ __forceinline__ void cp_async16(uint32_t dst, const void* src) {
    asm volatile("cp.async.cg.shared.global [%0], [%1], 16;" ::"r"(dst), "l"(src));
}
__device__ __forceinline__ void cp_commit() { asm volatile("cp.async.commit_group;"); }
template <int N> __device__ __forceinline__ void cp_wait() { asm volatile("cp.async.wait_group %0;" ::"n"(N) : "memory"); }
__device__ __forceinline__ void fence_async_proxy() { asm volatile("fence.proxy.async.shared::cta;" ::: "memory"); }
__device__ __forceinline__ float bf16_round(float x) { return __bfloat162float(__float2bfloat16_rn(x)); }
__device__ __forceinline__ uint32_t pack_bf16(float lo, float hi) {
    uint32_t p;
    asm("cvt.rn.bf16x2.f32 %0, %1, %2;" : "=r"(p) : "f"(hi), "f"(lo));
    return p;
}
__device__ __forceinline__ float bf_lo(uint32_t v) { return __uint_as_float(v << 16); }
__device__ __forceinline__ float bf_hi(uint32_t v) { return __uint_as_float(v & 0xffff0000u); }
__device__ __forceinline__ uint32_t pack_f16(float lo, float hi) {
    uint32_t p;
    asm("cvt.rn.f16x2.f32 %0, %1, %2;" : "=r"(p) : "f"(hi), "f"(lo));
    return p;
}
__device__ __forceinline__ float2 unpack_f16(uint32_t v) { return __half22float2(*reinterpret_cast<__half2*>(&v)); }
__device__ __forceinline__ float rcp_approx(float x) { float r; asm("rcp.approx.ftz.f32 %0, %1;" : "=f"(r) : "f"(x)); return r; }
__device__ __forceinline__ float sqrt_approx(float x) { float r; asm("sqrt.approx.ftz.f32 %0, %1;" : "=f"(r) : "f"(x)); return r; }

#define WG_FENCE() asm volatile("wgmma.fence.sync.aligned;" ::: "memory")
#define WG_COMMIT() asm volatile("wgmma.commit_group.sync.aligned;" ::: "memory")
#define WG_WAIT(n) asm volatile("wgmma.wait_group.sync.aligned " #n ";" ::: "memory")
#define R8(b) "+f"(d[b + 0]), "+f"(d[b + 1]), "+f"(d[b + 2]), "+f"(d[b + 3]), "+f"(d[b + 4]), "+f"(d[b + 5]), "+f"(d[b + 6]), "+f"(d[b + 7])

__device__ __forceinline__ uint64_t mkdesc(uint32_t saddr, uint32_t sbo16, uint32_t lbo16 = 8) {
    uint32_t lo = ((saddr & 0x3FFFF) >> 4) | (lbo16 << 16);
    uint64_t d;
    asm("mov.b64 %0, {%1, %2};" : "=l"(d) : "r"(lo), "r"(sbo16));
    return d;
}
__device__ __forceinline__ uint64_t mkdesc_sw128(uint32_t saddr, uint32_t lbo16) {
    uint32_t lo = ((saddr & 0x3FFFF) >> 4) | (lbo16 << 16);
    uint64_t d;
    asm("mov.b64 %0, {%1, %2};" : "=l"(d) : "r"(lo), "r"(0x40000040u));
    return d;
}
template <int N> __device__ __forceinline__ void fence_regs(float* D) {
#pragma unroll
    for (int i = 0; i < N; i++) asm volatile("" : "+f"(D[i])::"memory");
}

__device__ __forceinline__ void wg_bf16_n64(float* d, uint64_t da, uint64_t db) {
    asm volatile(
        "wgmma.mma_async.sync.aligned.m64n64k16.f32.bf16.bf16 "
        "{%0,%1,%2,%3,%4,%5,%6,%7,%8,%9,%10,%11,%12,%13,%14,%15,%16,%17,%18,%19,%20,%21,%22,%23,%24,%25,%26,%27,%28,%29,%30,%31},"
        " %32, %33, 1, 1, 1, 0, 1;"
        : R8(0), R8(8), R8(16), R8(24)
        : "l"(da), "l"(db));
}
__device__ __forceinline__ void wg_bf16_n144(float* d, uint64_t da, uint64_t db) {
    asm volatile(
        "wgmma.mma_async.sync.aligned.m64n144k16.f32.bf16.bf16 "
        "{%0,%1,%2,%3,%4,%5,%6,%7,%8,%9,%10,%11,%12,%13,%14,%15,%16,%17,%18,%19,%20,%21,%22,%23,%24,%25,%26,%27,%28,%29,%30,%31,"
        "%32,%33,%34,%35,%36,%37,%38,%39,%40,%41,%42,%43,%44,%45,%46,%47,%48,%49,%50,%51,%52,%53,%54,%55,%56,%57,%58,%59,%60,%61,%62,%63,"
        "%64,%65,%66,%67,%68,%69,%70,%71}, %72, %73, 1, 1, 1, 0, 1;"
        : R8(0), R8(8), R8(16), R8(24), R8(32), R8(40), R8(48), R8(56), R8(64)
        : "l"(da), "l"(db));
}

constexpr int G_ABYTES = 128 * 128;
constexpr int G_BBLK = 64 * 128;
constexpr int P_STAGES = 5;
constexpr int P_STAGE = G_ABYTES + 3 * G_BBLK;
constexpr int O_ASTAGES = 5;
constexpr int O_BOFF = O_ASTAGES * G_ABYTES;

__device__ __forceinline__ unsigned int ld_acquire(const unsigned int* p) {
    unsigned int v;
    asm volatile("ld.acquire.gpu.global.u32 %0, [%1];" : "=r"(v) : "l"(p) : "memory");
    return v;
}
__device__ __forceinline__ unsigned int ld_relaxed(const unsigned int* p) {
    unsigned int v;
    asm volatile("ld.relaxed.gpu.global.u32 %0, [%1];" : "=r"(v) : "l"(p) : "memory");
    return v;
}
__device__ __forceinline__ void bar_arrive(int id) {
    asm volatile("red.release.gpu.global.add.u32 [%0], 1;" ::"l"(&g_bar[id][0]) : "memory");
}
__device__ __forceinline__ void bar_wait(const unsigned int* p, unsigned int target) {
    long long t0 = clock64();
    while ((int)(ld_acquire(p) - target) < 0) {
        if (clock64() - t0 > 4000000000ll) __trap();
    }
}

#define ATT_POLY 1
#define ATT_MODE 0
#define ATT_MASK 0x2828
constexpr int A_NT = 128;
constexpr int A_NTH = 256;
constexpr uint32_t A_MASK = ATT_MASK;
__host__ __device__ constexpr int popc16(uint32_t m) { int c = 0; for (int i = 0; i < 16; i++) c += (m >> i) & 1; return c; }
constexpr int A_NM = 8 * popc16(A_MASK);
constexpr int A_NP = A_NT - A_NM;
constexpr float A_F0 = (ATT_POLY == 1) ? (15.f - 0.59368f) : (16.f - 1.71838f);
constexpr float A_MUS = (ATT_POLY == 1) ? 1.f : 2.f;
constexpr float A_LO = -A_F0 + 0.1f;
constexpr float A_HI = ((ATT_POLY == 1) ? 29.9f : 28.9f) - A_F0;
constexpr float A_BMAX = (-A_LO < A_HI) ? -A_LO : A_HI;
#define ATT_FL 4
constexpr int A_FL = ATT_FL;
constexpr float A_VS = 1.f / (256.f * A_FL);
constexpr float A_LMIN = 32.f * A_VS;
constexpr float A_C = 0.25f * 1.4426950408889634f;

constexpr int SM_K = 0;
constexpr int SM_V = 65536;
constexpr int SM_Q = SM_V + 98304;
constexpr int SM_N = SM_Q + 32768;
constexpr int SM_B = SM_N + 4096;
constexpr int SM_S = SM_B + 1024;
constexpr int SM_L = SM_S + 128;
constexpr int SM_TOTAL = O_BOFF + 16 * G_BBLK;
static_assert(P_STAGES * P_STAGE <= SM_TOTAL && SM_L + 2048 + 8192 <= SM_TOTAL, "smem");

__device__ __forceinline__ void bump(uint64_t& d, uint32_t inc16) {
    asm volatile("{.reg .b32 lo, hi; mov.b64 {lo, hi}, %0; add.u32 lo, lo, %1; mov.b64 %0, {lo, hi};}" : "+l"(d) : "r"(inc16));
}
template <int N> __device__ __forceinline__ void wg_qk32(float* d, const uint32_t* a, uint64_t desc);
template <int N> __device__ __forceinline__ void wg_qk16(uint32_t* d, const uint32_t* a, uint64_t desc);
template <> __device__ __forceinline__ void wg_qk32<80>(float* d, const uint32_t* a, uint64_t desc) {
    asm volatile("wgmma.mma_async.sync.aligned.m64n80k16.f32.f16.f16 {%0,%1,%2,%3,%4,%5,%6,%7,%8,%9,%10,%11,%12,%13,%14,%15,%16,%17,%18,%19,%20,%21,%22,%23,%24,%25,%26,%27,%28,%29,%30,%31,%32,%33,%34,%35,%36,%37,%38,%39}, {%40,%41,%42,%43}, %44, 1, 1, 1, 0;"
                 : "+f"(d[0]), "+f"(d[1]), "+f"(d[2]), "+f"(d[3]), "+f"(d[4]), "+f"(d[5]), "+f"(d[6]), "+f"(d[7]), "+f"(d[8]), "+f"(d[9]), "+f"(d[10]), "+f"(d[11]), "+f"(d[12]), "+f"(d[13]), "+f"(d[14]), "+f"(d[15]), "+f"(d[16]), "+f"(d[17]), "+f"(d[18]), "+f"(d[19]), "+f"(d[20]), "+f"(d[21]), "+f"(d[22]), "+f"(d[23]), "+f"(d[24]), "+f"(d[25]), "+f"(d[26]), "+f"(d[27]), "+f"(d[28]), "+f"(d[29]), "+f"(d[30]), "+f"(d[31]), "+f"(d[32]), "+f"(d[33]), "+f"(d[34]), "+f"(d[35]), "+f"(d[36]), "+f"(d[37]), "+f"(d[38]), "+f"(d[39])
                 : "r"(a[0]), "r"(a[1]), "r"(a[2]), "r"(a[3]), "l"(desc));
}
template <> __device__ __forceinline__ void wg_qk32<88>(float* d, const uint32_t* a, uint64_t desc) {
    asm volatile("wgmma.mma_async.sync.aligned.m64n88k16.f32.f16.f16 {%0,%1,%2,%3,%4,%5,%6,%7,%8,%9,%10,%11,%12,%13,%14,%15,%16,%17,%18,%19,%20,%21,%22,%23,%24,%25,%26,%27,%28,%29,%30,%31,%32,%33,%34,%35,%36,%37,%38,%39,%40,%41,%42,%43}, {%44,%45,%46,%47}, %48, 1, 1, 1, 0;"
                 : "+f"(d[0]), "+f"(d[1]), "+f"(d[2]), "+f"(d[3]), "+f"(d[4]), "+f"(d[5]), "+f"(d[6]), "+f"(d[7]), "+f"(d[8]), "+f"(d[9]), "+f"(d[10]), "+f"(d[11]), "+f"(d[12]), "+f"(d[13]), "+f"(d[14]), "+f"(d[15]), "+f"(d[16]), "+f"(d[17]), "+f"(d[18]), "+f"(d[19]), "+f"(d[20]), "+f"(d[21]), "+f"(d[22]), "+f"(d[23]), "+f"(d[24]), "+f"(d[25]), "+f"(d[26]), "+f"(d[27]), "+f"(d[28]), "+f"(d[29]), "+f"(d[30]), "+f"(d[31]), "+f"(d[32]), "+f"(d[33]), "+f"(d[34]), "+f"(d[35]), "+f"(d[36]), "+f"(d[37]), "+f"(d[38]), "+f"(d[39]), "+f"(d[40]), "+f"(d[41]), "+f"(d[42]), "+f"(d[43])
                 : "r"(a[0]), "r"(a[1]), "r"(a[2]), "r"(a[3]), "l"(desc));
}
template <> __device__ __forceinline__ void wg_qk32<96>(float* d, const uint32_t* a, uint64_t desc) {
    asm volatile("wgmma.mma_async.sync.aligned.m64n96k16.f32.f16.f16 {%0,%1,%2,%3,%4,%5,%6,%7,%8,%9,%10,%11,%12,%13,%14,%15,%16,%17,%18,%19,%20,%21,%22,%23,%24,%25,%26,%27,%28,%29,%30,%31,%32,%33,%34,%35,%36,%37,%38,%39,%40,%41,%42,%43,%44,%45,%46,%47}, {%48,%49,%50,%51}, %52, 1, 1, 1, 0;"
                 : "+f"(d[0]), "+f"(d[1]), "+f"(d[2]), "+f"(d[3]), "+f"(d[4]), "+f"(d[5]), "+f"(d[6]), "+f"(d[7]), "+f"(d[8]), "+f"(d[9]), "+f"(d[10]), "+f"(d[11]), "+f"(d[12]), "+f"(d[13]), "+f"(d[14]), "+f"(d[15]), "+f"(d[16]), "+f"(d[17]), "+f"(d[18]), "+f"(d[19]), "+f"(d[20]), "+f"(d[21]), "+f"(d[22]), "+f"(d[23]), "+f"(d[24]), "+f"(d[25]), "+f"(d[26]), "+f"(d[27]), "+f"(d[28]), "+f"(d[29]), "+f"(d[30]), "+f"(d[31]), "+f"(d[32]), "+f"(d[33]), "+f"(d[34]), "+f"(d[35]), "+f"(d[36]), "+f"(d[37]), "+f"(d[38]), "+f"(d[39]), "+f"(d[40]), "+f"(d[41]), "+f"(d[42]), "+f"(d[43]), "+f"(d[44]), "+f"(d[45]), "+f"(d[46]), "+f"(d[47])
                 : "r"(a[0]), "r"(a[1]), "r"(a[2]), "r"(a[3]), "l"(desc));
}
template <> __device__ __forceinline__ void wg_qk16<48>(uint32_t* d, const uint32_t* a, uint64_t desc) {
    asm volatile("wgmma.mma_async.sync.aligned.m64n48k16.f16.f16.f16 {%0,%1,%2,%3,%4,%5,%6,%7,%8,%9,%10,%11}, {%12,%13,%14,%15}, %16, 0, 1, 1, 0;"
                 : "=r"(d[0]), "=r"(d[1]), "=r"(d[2]), "=r"(d[3]), "=r"(d[4]), "=r"(d[5]), "=r"(d[6]), "=r"(d[7]), "=r"(d[8]), "=r"(d[9]), "=r"(d[10]), "=r"(d[11])
                 : "r"(a[0]), "r"(a[1]), "r"(a[2]), "r"(a[3]), "l"(desc));
}
template <> __device__ __forceinline__ void wg_qk16<40>(uint32_t* d, const uint32_t* a, uint64_t desc) {
    asm volatile("wgmma.mma_async.sync.aligned.m64n40k16.f16.f16.f16 {%0,%1,%2,%3,%4,%5,%6,%7,%8,%9}, {%10,%11,%12,%13}, %14, 0, 1, 1, 0;"
                 : "=r"(d[0]), "=r"(d[1]), "=r"(d[2]), "=r"(d[3]), "=r"(d[4]), "=r"(d[5]), "=r"(d[6]), "=r"(d[7]), "=r"(d[8]), "=r"(d[9])
                 : "r"(a[0]), "r"(a[1]), "r"(a[2]), "r"(a[3]), "l"(desc));
}
template <> __device__ __forceinline__ void wg_qk16<32>(uint32_t* d, const uint32_t* a, uint64_t desc) {
    asm volatile("wgmma.mma_async.sync.aligned.m64n32k16.f16.f16.f16 {%0,%1,%2,%3,%4,%5,%6,%7}, {%8,%9,%10,%11}, %12, 0, 1, 1, 0;"
                 : "=r"(d[0]), "=r"(d[1]), "=r"(d[2]), "=r"(d[3]), "=r"(d[4]), "=r"(d[5]), "=r"(d[6]), "=r"(d[7])
                 : "r"(a[0]), "r"(a[1]), "r"(a[2]), "r"(a[3]), "l"(desc));
}
template <> __device__ __forceinline__ void wg_qk32<128>(float* d, const uint32_t* a, uint64_t desc) {
    asm volatile("wgmma.mma_async.sync.aligned.m64n128k16.f32.f16.f16 {%0,%1,%2,%3,%4,%5,%6,%7,%8,%9,%10,%11,%12,%13,%14,%15,%16,%17,%18,%19,%20,%21,%22,%23,%24,%25,%26,%27,%28,%29,%30,%31,%32,%33,%34,%35,%36,%37,%38,%39,%40,%41,%42,%43,%44,%45,%46,%47,%48,%49,%50,%51,%52,%53,%54,%55,%56,%57,%58,%59,%60,%61,%62,%63}, {%64,%65,%66,%67}, %68, 1, 1, 1, 0;"
                 : "+f"(d[0]), "+f"(d[1]), "+f"(d[2]), "+f"(d[3]), "+f"(d[4]), "+f"(d[5]), "+f"(d[6]), "+f"(d[7]), "+f"(d[8]), "+f"(d[9]), "+f"(d[10]), "+f"(d[11]), "+f"(d[12]), "+f"(d[13]), "+f"(d[14]), "+f"(d[15]), "+f"(d[16]), "+f"(d[17]), "+f"(d[18]), "+f"(d[19]), "+f"(d[20]), "+f"(d[21]), "+f"(d[22]), "+f"(d[23]), "+f"(d[24]), "+f"(d[25]), "+f"(d[26]), "+f"(d[27]), "+f"(d[28]), "+f"(d[29]), "+f"(d[30]), "+f"(d[31]), "+f"(d[32]), "+f"(d[33]), "+f"(d[34]), "+f"(d[35]), "+f"(d[36]), "+f"(d[37]), "+f"(d[38]), "+f"(d[39]), "+f"(d[40]), "+f"(d[41]), "+f"(d[42]), "+f"(d[43]), "+f"(d[44]), "+f"(d[45]), "+f"(d[46]), "+f"(d[47]), "+f"(d[48]), "+f"(d[49]), "+f"(d[50]), "+f"(d[51]), "+f"(d[52]), "+f"(d[53]), "+f"(d[54]), "+f"(d[55]), "+f"(d[56]), "+f"(d[57]), "+f"(d[58]), "+f"(d[59]), "+f"(d[60]), "+f"(d[61]), "+f"(d[62]), "+f"(d[63])
                 : "r"(a[0]), "r"(a[1]), "r"(a[2]), "r"(a[3]), "l"(desc));
}
template <int N> __device__ __forceinline__ void wg_qk32z(float* d, const uint32_t* a, uint64_t desc);
template <> __device__ __forceinline__ void wg_qk32z<48>(float* d, const uint32_t* a, uint64_t desc) {
    asm volatile("wgmma.mma_async.sync.aligned.m64n48k16.f32.f16.f16 {%0,%1,%2,%3,%4,%5,%6,%7,%8,%9,%10,%11,%12,%13,%14,%15,%16,%17,%18,%19,%20,%21,%22,%23}, {%24,%25,%26,%27}, %28, 0, 1, 1, 0;"
                 : "=f"(d[0]), "=f"(d[1]), "=f"(d[2]), "=f"(d[3]), "=f"(d[4]), "=f"(d[5]), "=f"(d[6]), "=f"(d[7]), "=f"(d[8]), "=f"(d[9]), "=f"(d[10]), "=f"(d[11]), "=f"(d[12]), "=f"(d[13]), "=f"(d[14]), "=f"(d[15]), "=f"(d[16]), "=f"(d[17]), "=f"(d[18]), "=f"(d[19]), "=f"(d[20]), "=f"(d[21]), "=f"(d[22]), "=f"(d[23])
                 : "r"(a[0]), "r"(a[1]), "r"(a[2]), "r"(a[3]), "l"(desc));
}
template <> __device__ __forceinline__ void wg_qk32z<40>(float* d, const uint32_t* a, uint64_t desc) {
    asm volatile("wgmma.mma_async.sync.aligned.m64n40k16.f32.f16.f16 {%0,%1,%2,%3,%4,%5,%6,%7,%8,%9,%10,%11,%12,%13,%14,%15,%16,%17,%18,%19}, {%20,%21,%22,%23}, %24, 0, 1, 1, 0;"
                 : "=f"(d[0]), "=f"(d[1]), "=f"(d[2]), "=f"(d[3]), "=f"(d[4]), "=f"(d[5]), "=f"(d[6]), "=f"(d[7]), "=f"(d[8]), "=f"(d[9]), "=f"(d[10]), "=f"(d[11]), "=f"(d[12]), "=f"(d[13]), "=f"(d[14]), "=f"(d[15]), "=f"(d[16]), "=f"(d[17]), "=f"(d[18]), "=f"(d[19])
                 : "r"(a[0]), "r"(a[1]), "r"(a[2]), "r"(a[3]), "l"(desc));
}
template <> __device__ __forceinline__ void wg_qk32z<32>(float* d, const uint32_t* a, uint64_t desc) {
    asm volatile("wgmma.mma_async.sync.aligned.m64n32k16.f32.f16.f16 {%0,%1,%2,%3,%4,%5,%6,%7,%8,%9,%10,%11,%12,%13,%14,%15}, {%16,%17,%18,%19}, %20, 0, 1, 1, 0;"
                 : "=f"(d[0]), "=f"(d[1]), "=f"(d[2]), "=f"(d[3]), "=f"(d[4]), "=f"(d[5]), "=f"(d[6]), "=f"(d[7]), "=f"(d[8]), "=f"(d[9]), "=f"(d[10]), "=f"(d[11]), "=f"(d[12]), "=f"(d[13]), "=f"(d[14]), "=f"(d[15])
                 : "r"(a[0]), "r"(a[1]), "r"(a[2]), "r"(a[3]), "l"(desc));
}
__device__ __forceinline__ void wg_pv24h(uint32_t* d, const uint32_t* a, uint64_t desc) {
    asm volatile(
        "wgmma.mma_async.sync.aligned.m64n24k16.f16.f16.f16 {%0,%1,%2,%3,%4,%5}, {%6,%7,%8,%9}, %10, 1, 1, 1, 1;"
        : "+r"(d[0]), "+r"(d[1]), "+r"(d[2]), "+r"(d[3]), "+r"(d[4]), "+r"(d[5])
        : "r"(a[0]), "r"(a[1]), "r"(a[2]), "r"(a[3]), "l"(desc));
}
__device__ __forceinline__ uint32_t poly_pair(float y0, float y1) {
    uint32_t z, w, t;
    asm("prmt.b32 %0, %1, %2, 0x6521;" : "=r"(z) : "f"(y0), "f"(y1));
    asm("lop3.b32 %0, %1, 0x03ff03ff, 0x38003800, 0xEA;" : "=r"(w) : "r"(z));
    asm("fma.rn.f16x2 %0, %1, %1, %2;" : "=r"(t) : "r"(w), "r"(0x380b380b));
    return z + t - w;
}
__device__ __constant__ uint32_t c65536 = 65536u;
__device__ __forceinline__ uint32_t mufu_pair(uint32_t x) {
    uint32_t p;
    asm("ex2.approx.f16x2 %0, %1;" : "=r"(p) : "r"(x));
    return p;
}
__device__ __forceinline__ uint32_t mufu_pair32(float x0, float x1) {
    float a, b;
    asm("ex2.approx.ftz.f32 %0, %1;" : "=f"(a) : "f"(x0));
    asm("ex2.approx.ftz.f32 %0, %1;" : "=f"(b) : "f"(x1));
    return pack_f16(a, b);
}
struct Scores { float p[64]; };
__device__ __forceinline__ void fence_scores(Scores& D) { fence_regs<64>(D.p); }
#define WG_QK(D, a, dp, dm) wg_qk32<128>(D.p, a, dp)
#define MUFU_P(D, i) mufu_pair32(D.p[A_NP / 2 + 2 * (i)], D.p[A_NP / 2 + 2 * (i) + 1])
template <int J0, int J1>
__device__ __forceinline__ void exp_block(const Scores& D, uint32_t* P) {
#pragma unroll
    for (int j = J0; j < J1; j++) {
        const int im = popc16(A_MASK & ((1u << j) - 1)), ip = j - im;
        if ((A_MASK >> j) & 1) {
            P[2 * (j - J0)] = MUFU_P(D, 2 * im);
            P[2 * (j - J0) + 1] = MUFU_P(D, 2 * im + 1);
        } else {
            P[2 * (j - J0)] = poly_pair(D.p[4 * ip], D.p[4 * ip + 1]);
            P[2 * (j - J0) + 1] = poly_pair(D.p[4 * ip + 2], D.p[4 * ip + 3]);
        }
    }
}

__device__ __forceinline__ float pow2_norm(uint32_t vbits) {
    int e = (int)((vbits >> 23) & 0xff);
    e = min(max(e, 16), 240);
    return __uint_as_float((uint32_t)(253 - e) << 23);
}
__device__ __forceinline__ float pow2_inv(float p) { return __uint_as_float(0x7f000000u - __float_as_uint(p)); }
__device__ __forceinline__ int f2ord(float f) { int i = __float_as_int(f); return i ^ ((i >> 31) & 0x7fffffff); }
__device__ __forceinline__ float ord2f(int i) { return __int_as_float(i ^ ((i >> 31) & 0x7fffffff)); }

__device__ __noinline__ void attn_safe_row(int br, int row, int head, int t4, unsigned qmask) {
    float q[DH], o[DH];
    const __nv_bfloat16* qp = &g_Q[br][row][head * DH];
#pragma unroll
    for (int t = 0; t < 4; t++) {
        q[2 * t] = __bfloat162float(qp[4 * t]) * A_C;
        q[2 * t + 1] = __bfloat162float(qp[4 * t + 1]) * A_C;
        q[8 + 2 * t] = __bfloat162float(qp[4 * t + 2]) * A_C;
        q[9 + 2 * t] = __bfloat162float(qp[4 * t + 3]) * A_C;
    }
#pragma unroll
    for (int d = 0; d < DH; d++) o[d] = 0.f;
    float m = -INFINITY, l = 0.f;
    for (int j = t4; j < S_LEN; j += 4) {
        uint4 k0 = *reinterpret_cast<const uint4*>(&g_K[br][j][0]);
        uint4 k1 = *reinterpret_cast<const uint4*>(&g_K[br][j][8]);
        uint4 v0 = *reinterpret_cast<const uint4*>(&g_V[br][j][0]);
        uint4 v1 = *reinterpret_cast<const uint4*>(&g_V[br][j][8]);
        const uint32_t kk[8] = {k0.x, k0.y, k0.z, k0.w, k1.x, k1.y, k1.z, k1.w};
        const uint32_t vv[8] = {v0.x, v0.y, v0.z, v0.w, v1.x, v1.y, v1.z, v1.w};
        float s = 0.f;
#pragma unroll
        for (int d = 0; d < 8; d++) s += q[2 * d] * bf_lo(kk[d]) + q[2 * d + 1] * bf_hi(kk[d]);
        float mn = fmaxf(m, s);
        float c = exp2f(m - mn), p = exp2f(s - mn);
        if (mn == -INFINITY) { c = 1.f; p = 0.f; }
        l = l * c + p;
#pragma unroll
        for (int d = 0; d < 8; d++) {
            o[2 * d] = o[2 * d] * c + p * bf_lo(vv[d]);
            o[2 * d + 1] = o[2 * d + 1] * c + p * bf_hi(vv[d]);
        }
        m = mn;
    }
    float mm = fmaxf(m, __shfl_xor_sync(qmask, m, 1));
    mm = fmaxf(mm, __shfl_xor_sync(qmask, mm, 2));
    float c = (mm == -INFINITY) ? 1.f : exp2f(m - mm);
    l *= c;
    l += __shfl_xor_sync(qmask, l, 1);
    l += __shfl_xor_sync(qmask, l, 2);
    float inv = 1.f / l;
    __nv_bfloat16* op = &g_O[br][row][head * DH];
#pragma unroll
    for (int d = 0; d < DH; d++) {
        float v = o[d] * c;
        v += __shfl_xor_sync(qmask, v, 1);
        v += __shfl_xor_sync(qmask, v, 2);
        if ((d >> 2) == t4) op[d] = __float2bfloat16_rn(v * inv);
    }
}

__device__ __forceinline__ void flush_acc(float* O, uint32_t* H) {
#pragma unroll
    for (int i = 0; i < 6; i++) asm volatile("" : "+r"(H[i])::"memory");
#pragma unroll
    for (int i = 0; i < 4; i++) { float2 f = unpack_f16(H[i]); O[2 * i] += f.x; O[2 * i + 1] += f.y; }
    O[8] += unpack_f16(H[4]).x;
    O[9] += unpack_f16(H[5]).x;
#pragma unroll
    for (int i = 0; i < 6; i++) H[i] = 0u;
}

__device__ __forceinline__ void attn_loop(float* OA, float* OB, const uint32_t* qA, const uint32_t* qB, uint32_t sK, uint32_t sV) {
    Scores DA, DB;
    uint32_t P0[16], P1[16];
    uint32_t HA[6] = {0u, 0u, 0u, 0u, 0u, 0u}, HB[6] = {0u, 0u, 0u, 0u, 0u, 0u};
#pragma unroll
    for (int i = 0; i < A_NP / 2; i++) DA.p[i] = DB.p[i] = 2.f + A_F0 * 0.0625f + 3.0517578125e-5f;
#pragma unroll
    for (int i = A_NP / 2; i < 64; i++) DA.p[i] = DB.p[i] = 0.f;
#pragma unroll
    for (int i = 0; i < 10; i++) OA[i] = OB[i] = 0.f;
    uint64_t dpA = mkdesc(sK, 16), dpB = mkdesc(sK, 16), dmA = mkdesc(sK + A_NP * 32, 16), dmB = mkdesc(sK + A_NP * 32, 16);
    uint64_t dv[8];
#pragma unroll
    for (int j = 0; j < 8; j++) dv[j] = mkdesc(sV + j * 768, 16);
    WG_FENCE();
    WG_QK(DA, qA, dpA, dmA);
    WG_COMMIT();
    WG_WAIT(0);
    fence_scores(DA);
#pragma unroll 1
    for (int grp = 0; grp < S_LEN / A_NT / A_FL; grp++) {
#pragma unroll 1
        for (int t = 0; t < A_FL; t++) {
            WG_FENCE();
            WG_QK(DB, qB, dpB, dmB);
            WG_COMMIT();
            bump(dpB, A_NT * 2); bump(dpA, A_NT * 2);
            exp_block<0, 8>(DA, P0);
            WG_FENCE();
#pragma unroll
            for (int j = 0; j < 4; j++) wg_pv24h(HA, &P0[4 * j], dv[j]);
            WG_COMMIT();
            WG_WAIT(2);
            exp_block<8, 16>(DA, P1);
            WG_FENCE();
#pragma unroll
            for (int j = 4; j < 8; j++) wg_pv24h(HA, &P1[4 * (j - 4)], dv[j]);
            WG_COMMIT();
            WG_WAIT(1);
            fence_scores(DB);
            WG_FENCE();
            WG_QK(DA, qA, dpA, dmA);
            WG_COMMIT();
            exp_block<0, 8>(DB, P0);
            WG_FENCE();
#pragma unroll
            for (int j = 0; j < 4; j++) { wg_pv24h(HB, &P0[4 * j], dv[j]); bump(dv[j], A_NT * 3); }
            WG_COMMIT();
            WG_WAIT(2);
            exp_block<8, 16>(DB, P1);
            WG_FENCE();
#pragma unroll
            for (int j = 4; j < 8; j++) { wg_pv24h(HB, &P1[4 * (j - 4)], dv[j]); bump(dv[j], A_NT * 3); }
            WG_COMMIT();
            WG_WAIT(1);
            fence_scores(DA);
        }
        flush_acc(OA, HA);
        WG_WAIT(0);
        flush_acc(OB, HB);
    }
}

__device__ __forceinline__ uint32_t finish_rows(const float* O, const unsigned char* flag, const float4 ib, __nv_bfloat16* dst) {
    const bool bad0 = flag[0] || !(O[8] >= A_LMIN && O[8] < 1e30f);
    const bool bad1 = flag[8] || !(O[9] >= A_LMIN && O[9] < 1e30f);
    const float i0 = rcp_approx(O[8]), i1 = rcp_approx(O[9]);
    uint2 a, b;
    a.x = pack_bf16(O[0] * i0 * ib.x, O[1] * i0 * ib.y);
    a.y = pack_bf16(O[4] * i0 * ib.z, O[5] * i0 * ib.w);
    b.x = pack_bf16(O[2] * i1 * ib.x, O[3] * i1 * ib.y);
    b.y = pack_bf16(O[6] * i1 * ib.z, O[7] * i1 * ib.w);
    *reinterpret_cast<uint2*>(dst) = a;
    *reinterpret_cast<uint2*>(dst + 8 * DM) = b;
    return (bad0 ? 1u : 0u) | (bad1 ? 2u : 0u);
}

__device__ __forceinline__ void stash_q(unsigned char* smem, uint2 a, uint2 b, float cq, int h, int rloc, int t4) {
    const uint32_t q0 = pack_f16(bf_lo(a.x) * cq, bf_hi(a.x) * cq), q2 = pack_f16(bf_lo(a.y) * cq, bf_hi(a.y) * cq);
    const uint32_t q1 = pack_f16(bf_lo(b.x) * cq, bf_hi(b.x) * cq), q3 = pack_f16(bf_lo(b.y) * cq, bf_hi(b.y) * cq);
    *reinterpret_cast<uint2*>(smem + SM_Q + rloc * 256 + h * 32 + t4 * 8) = make_uint2(q0, q2);
    *reinterpret_cast<uint2*>(smem + SM_Q + (rloc + 8) * 256 + h * 32 + t4 * 8) = make_uint2(q1, q3);
    const float2 f0 = unpack_f16(q0), f2 = unpack_f16(q2), f1 = unpack_f16(q1), f3 = unpack_f16(q3);
    float n0 = f0.x * f0.x + f0.y * f0.y + f2.x * f2.x + f2.y * f2.y;
    float n1 = f1.x * f1.x + f1.y * f1.y + f3.x * f3.x + f3.y * f3.y;
    n0 += __shfl_xor_sync(0xffffffffu, n0, 1); n0 += __shfl_xor_sync(0xffffffffu, n0, 2);
    n1 += __shfl_xor_sync(0xffffffffu, n1, 1); n1 += __shfl_xor_sync(0xffffffffu, n1, 2);
    float* sn = reinterpret_cast<float*>(smem + SM_N) + h * 128 + rloc;
    if (t4 == 0) { sn[0] = n0; sn[8] = n1; }
}

struct Params {
    const __nv_bfloat16 *x, *wq[2], *wk[2], *wv[2], *wo[2], *gate_w;
    __nv_bfloat16* out;
};

__global__ void __launch_bounds__(A_NTH, 1) fused_kernel(const Params prm) {
    extern __shared__ __align__(1024) unsigned char smem[];
    const int tid = threadIdx.x, lane = tid & 31, warp = tid >> 5;
    const int wg = tid >> 7, warp_in_wg = warp & 3;
    const int br = blockIdx.x >> 6;
    const int qb = (blockIdx.x >> 2) & 15;
    const int hg = blockIdx.x & 3;
    __shared__ uint32_t s_stat[32];
    if (tid < 32) s_stat[tid] = 0u;
    const uint32_t sbase = smem_u32(smem);
    const int c8 = lane & 7, r4 = lane >> 3;
    const int g = lane >> 2, t4 = lane & 3;
    const int rloc = wg * 64 + warp_in_wg * 16 + g;
    const int row0 = qb * 128 + rloc;
    TL(0, 0);
    const unsigned int gen1 = ld_relaxed(&g_bar[br][0]) >> 6, gen2 = ld_relaxed(&g_flag[qb][br * 4 + hg]);
    uint32_t* stat = g_stat[gen1 & 1][br];

    const int grow = qb * 128 + (br * 4 + hg) * 16 + warp * 2;
    uint4 gw0, gw1, gx[2][2];
    uint2 qpk[8][2];
    {
        const __nv_bfloat16* A = prm.x + (size_t)qb * 128 * DM;
        const __nv_bfloat16* Wq = (br ? prm.wq[1] : prm.wq[0]) + hg * 128;
        const __nv_bfloat16* Wx = (hg == 1) ? (br ? prm.wv[1] : prm.wv[0]) : (br ? prm.wk[1] : prm.wk[0]);
        auto load = [&](int chunk) {
            const uint32_t sa = sbase + (chunk % P_STAGES) * P_STAGE, sb = sa + G_ABYTES;
            const int k0 = chunk * 64;
#pragma unroll
            for (int i = 0; i < 4; i++) {
                const int r = warp * 16 + i * 4 + r4;
                cp_async16(sa + r * 128 + ((c8 ^ (r & 7)) << 4), A + (size_t)r * DM + k0 + c8 * 8);
            }
#pragma unroll
            for (int i = 0; i < 4; i++) {
                const int kr = warp * 8 + i * 2 + (lane >> 4), nb = (lane >> 3) & 1;
                cp_async16(sb + nb * G_BBLK + kr * 128 + ((c8 ^ (kr & 7)) << 4), Wq + (size_t)(k0 + kr) * DM + nb * 64 + c8 * 8);
            }
            if (lane < 16) {
                const int kr = warp * 8 + (lane >> 1), c = lane & 1;
                cp_async16(sb + 2 * G_BBLK + kr * 128 + ((c ^ (kr & 7)) << 4), Wx + (size_t)(k0 + kr) * DH + c * 8);
            }
            cp_commit();
        };
#pragma unroll
        for (int c = 0; c < P_STAGES; c++) load(c);
        gw0 = *reinterpret_cast<const uint4*>(prm.gate_w + lane * 8);
        gw1 = *reinterpret_cast<const uint4*>(prm.gate_w + 256 + lane * 8);
#pragma unroll
        for (int r = 0; r < 2; r++) {
            gx[r][0] = *reinterpret_cast<const uint4*>(prm.x + (size_t)(grow + r) * DM + lane * 8);
            gx[r][1] = *reinterpret_cast<const uint4*>(prm.x + (size_t)(grow + r) * DM + 256 + lane * 8);
        }
        float acc[72];
#pragma unroll
        for (int i = 0; i < 72; i++) acc[i] = 0.f;
#pragma unroll
        for (int c = 0; c < 8; c++) {
            if (c == 0) cp_wait<P_STAGES - 1>(); else if (c == 1) cp_wait<P_STAGES - 2>(); else cp_wait<P_STAGES - 3>();
            fence_async_proxy();
            __syncthreads();
            if (c >= 2) { if (c - 2 + P_STAGES < 8) load(c - 2 + P_STAGES); else cp_commit(); }
            const uint32_t sa = sbase + (c % P_STAGES) * P_STAGE + wg * 8192, sb = sbase + (c % P_STAGES) * P_STAGE + G_ABYTES;
            WG_FENCE();
#pragma unroll
            for (int kk = 0; kk < 4; kk++) wg_bf16_n144(acc, mkdesc_sw128(sa + kk * 32, 1), mkdesc_sw128(sb + kk * 2048, G_BBLK / 16));
            WG_COMMIT();
            WG_WAIT(1);
        }
        WG_WAIT(0);
        fence_regs<72>(acc);
        TL(0, 1);
        if (hg < 2) {
            const uint32_t p0 = pack_bf16(acc[64], acc[65]), p1 = pack_bf16(acc[66], acc[67]);
            const uint32_t p2 = pack_bf16(acc[68], acc[69]), p3 = pack_bf16(acc[70], acc[71]);
            __nv_bfloat16* dst = hg ? &g_V[br][0][0] : &g_K[br][0][0];
            *reinterpret_cast<uint32_t*>(dst + row0 * DH + 2 * t4) = p0;
            *reinterpret_cast<uint32_t*>(dst + row0 * DH + 8 + 2 * t4) = p2;
            *reinterpret_cast<uint32_t*>(dst + (row0 + 8) * DH + 2 * t4) = p1;
            *reinterpret_cast<uint32_t*>(dst + (row0 + 8) * DH + 8 + 2 * t4) = p3;
            if (hg == 0) {
                float n0 = bf_lo(p0) * bf_lo(p0) + bf_hi(p0) * bf_hi(p0) + bf_lo(p2) * bf_lo(p2) + bf_hi(p2) * bf_hi(p2);
                float n1 = bf_lo(p1) * bf_lo(p1) + bf_hi(p1) * bf_hi(p1) + bf_lo(p3) * bf_lo(p3) + bf_hi(p3) * bf_hi(p3);
                n0 += __shfl_xor_sync(0xffffffffu, n0, 1); n0 += __shfl_xor_sync(0xffffffffu, n0, 2);
                n1 += __shfl_xor_sync(0xffffffffu, n1, 1); n1 += __shfl_xor_sync(0xffffffffu, n1, 2);
                if (!(n0 <= 3.0e38f)) n0 = 3.0e38f;
                if (!(n1 <= 3.0e38f)) n1 = 3.0e38f;
                float n = fmaxf(n0, n1);
#pragma unroll
                for (int o = 4; o < 32; o <<= 1) n = fmaxf(n, __shfl_xor_sync(0xffffffffu, n, o));
                if (lane == 0) atomicMax(&s_stat[0], __float_as_uint(n));
            } else {
                float v[4] = {fmaxf(fabsf(bf_lo(p0)), fabsf(bf_lo(p1))), fmaxf(fabsf(bf_hi(p0)), fabsf(bf_hi(p1))),
                              fmaxf(fabsf(bf_lo(p2)), fabsf(bf_lo(p3))), fmaxf(fabsf(bf_hi(p2)), fabsf(bf_hi(p3)))};
#pragma unroll
                for (int o = 4; o < 32; o <<= 1)
#pragma unroll
                    for (int i = 0; i < 4; i++) v[i] = fmaxf(v[i], __shfl_xor_sync(0xffffffffu, v[i], o));
                if (lane < 4) {
                    atomicMax(&s_stat[1 + 2 * t4], __float_as_uint(v[0]));
                    atomicMax(&s_stat[2 + 2 * t4], __float_as_uint(v[1]));
                    atomicMax(&s_stat[9 + 2 * t4], __float_as_uint(v[2]));
                    atomicMax(&s_stat[10 + 2 * t4], __float_as_uint(v[3]));
                }
            }
        }
        __syncthreads();
        if (warp == 0) {
            if (hg < 2 && lane < 17 && (hg == 0) == (lane == 0)) atomicMax(&stat[lane], s_stat[lane]);
            __syncwarp();
            if (lane == 0) bar_arrive(br);
        }
#pragma unroll
        for (int h = 0; h < 8; h++) {
            qpk[h][0].x = pack_bf16(acc[8 * h + 0], acc[8 * h + 1]); qpk[h][0].y = pack_bf16(acc[8 * h + 4], acc[8 * h + 5]);
            qpk[h][1].x = pack_bf16(acc[8 * h + 2], acc[8 * h + 3]); qpk[h][1].y = pack_bf16(acc[8 * h + 6], acc[8 * h + 7]);
            stash_q(smem, qpk[h][0], qpk[h][1], A_C / 16.f, h, rloc, t4);
        }
    }

    unsigned char* s_bad = smem + SM_B;
    float* s_ib = reinterpret_cast<float*>(smem + SM_S);
    int* l_cnt = reinterpret_cast<int*>(smem + SM_S + 64);
    unsigned short* l_id = reinterpret_cast<unsigned short*>(smem + SM_L);
    int* l_mx = reinterpret_cast<int*>(smem + SM_L + 2048);
    int* l_mn = l_mx + 1024;
    reinterpret_cast<uint32_t*>(s_bad)[tid] = 0u;
    TL(0, 2);
    if (warp == 0) {
        if (lane == 0) {
            *l_cnt = 0;
            bar_wait(&g_bar[br][0], (gen1 + 1) << 6);
        }
        __syncwarp();
        s_stat[lane] = __ldcg(&stat[lane]);
    }
    __syncthreads();
    TL(1, 1);
    if ((blockIdx.x & 63) == 0 && tid < 32) g_stat[(gen1 + 1) & 1][br][tid] = 0u;
    const int c = tid >> 1, hf = tid & 1;
    uint4 kr[16], vr[16];
#pragma unroll
    for (int t = 0; t < 16; t++) kr[t] = *reinterpret_cast<const uint4*>(&g_K[br][t * A_NT + c][hf * 8]);
    asm volatile("" ::: "memory");
#pragma unroll
    for (int h = 0; h < 8; h++) {
        *reinterpret_cast<uint2*>(&g_Q[br][row0][hg * 128 + h * 16 + t4 * 4]) = qpk[h][0];
        *reinterpret_cast<uint2*>(&g_Q[br][row0 + 8][hg * 128 + h * 16 + t4 * 4]) = qpk[h][1];
    }
    {
        const uint32_t wp[8] = {gw0.x, gw0.y, gw0.z, gw0.w, gw1.x, gw1.y, gw1.z, gw1.w};
#pragma unroll
        for (int r = 0; r < 2; r++) {
            const uint32_t xp[8] = {gx[r][0].x, gx[r][0].y, gx[r][0].z, gx[r][0].w, gx[r][1].x, gx[r][1].y, gx[r][1].z, gx[r][1].w};
            float sg = 0.f;
#pragma unroll
            for (int j = 0; j < 8; j++) {
                const uint32_t pr = pack_bf16(bf_lo(xp[j]) * bf_lo(wp[j]), bf_hi(xp[j]) * bf_hi(wp[j]));
                sg += bf_lo(pr);
                sg += bf_hi(pr);
            }
#pragma unroll
            for (int o = 16; o > 0; o >>= 1) sg += __shfl_xor_sync(0xffffffffu, sg, o);
            if (lane == 0) g_gate[grow + r] = bf16_round(rcp_approx(1.f + __expf(-bf16_round(sg))));
        }
    }
    const float kmax = sqrt_approx(__uint_as_float(s_stat[0]));
    const bool renorm = !(kmax >= 0.125f && kmax <= 128.f);
    const float alpha = renorm ? pow2_norm(__float_as_uint(kmax)) : 1.f;
    const float kmaxn = kmax * alpha * 16.04f;
    float beta[8];
#pragma unroll
    for (int i = 0; i < 8; i++) beta[i] = pow2_norm(s_stat[1 + hf * 8 + i]);
    if (tid < 2) {
#pragma unroll
        for (int i = 0; i < 8; i++) s_ib[hf * 8 + i] = pow2_inv(beta[i]);
    }
    if (renorm) {
        const float cq = (A_C / 16.f) * pow2_inv(alpha);
#pragma unroll
        for (int h = 0; h < 8; h++) stash_q(smem, qpk[h][0], qpk[h][1], cq, h, rloc, t4);
        __syncthreads();
    }
    {
        const float lim = (A_BMAX - 0.02f) * (A_BMAX - 0.02f);
        const float4 n4 = reinterpret_cast<const float4*>(smem + SM_N)[tid];
        const float nn[4] = {n4.x, n4.y, n4.z, n4.w};
#pragma unroll
        for (int i = 0; i < 4; i++) {
            if (!(nn[i] * kmaxn * kmaxn <= lim)) {
                const int e = atomicAdd(l_cnt, 1);
                l_id[e] = (unsigned short)(tid * 4 + i); l_mx[e] = INT_MIN; l_mn[e] = INT_MAX;
            }
        }
    }
#pragma unroll
    for (int t = 0; t < 16; t++) vr[t] = *reinterpret_cast<const uint4*>(&g_V[br][t * A_NT + c][hf * 8]);
    TL(1, 2);
    {
        const int j = c >> 3;
        const bool mu = (A_MASK >> j) & 1;
        const int im = __popc(A_MASK & ((1u << j) - 1));
        const int krow8 = mu ? (A_NP / 8 + im) : (j - im);
        const float ksc = mu ? alpha * 16.f : alpha;
        const float vsc = mu ? A_VS * A_MUS : A_VS;
        const uint32_t ones = pack_f16(vsc, vsc);
#pragma unroll
        for (int i = 0; i < 8; i++) beta[i] *= vsc;
        float acc[8];
#pragma unroll
        for (int i = 0; i < 8; i++) acc[i] = 0.f;
        unsigned char* kdst = smem + SM_K + krow8 * 256 + hf * 128 + (c & 7) * 16;
        unsigned char* vdst = smem + SM_V + (c >> 4) * 768 + ((c >> 3) & 1) * 128 + (c & 7) * 16 + hf * 8;
#pragma unroll
        for (int t = 0; t < 16; t++) {
            const uint32_t kk[4] = {kr[t].x, kr[t].y, kr[t].z, kr[t].w};
            uint32_t dd[4];
#pragma unroll
            for (int i = 0; i < 4; i++) {
                dd[i] = pack_f16(bf_lo(kk[i]) * ksc - acc[2 * i], bf_hi(kk[i]) * ksc - acc[2 * i + 1]);
                const float2 f = unpack_f16((mu && ATT_MODE != 0) ? 0u : dd[i]);
                acc[2 * i] += f.x; acc[2 * i + 1] += f.y;
            }
            *reinterpret_cast<uint4*>(kdst + t * (A_NT * 32)) = make_uint4(dd[0], dd[1], dd[2], dd[3]);
        }
#pragma unroll
        for (int t = 0; t < 16; t++) {
            const uint32_t v0 = pack_f16(bf_lo(vr[t].x) * beta[0], bf_hi(vr[t].x) * beta[1]);
            const uint32_t v1 = pack_f16(bf_lo(vr[t].y) * beta[2], bf_hi(vr[t].y) * beta[3]);
            const uint32_t v2 = pack_f16(bf_lo(vr[t].z) * beta[4], bf_hi(vr[t].z) * beta[5]);
            const uint32_t v3 = pack_f16(bf_lo(vr[t].w) * beta[6], bf_hi(vr[t].w) * beta[7]);
            unsigned char* vb = vdst + t * (A_NT * 48);
            *reinterpret_cast<uint2*>(vb) = make_uint2(v0, v2);
            *reinterpret_cast<uint2*>(vb + 256) = make_uint2(v1, v3);
            *reinterpret_cast<uint2*>(vb + 512) = make_uint2(ones, ones);
        }
    }
    fence_async_proxy();
    __syncthreads();
    const int n_list = *l_cnt;
    if (n_list > 0) {
        const float ssc = 16.f * alpha;
#pragma unroll 1
        for (int e = 0; e < n_list; e++) {
            const int id = l_id[e];
            const uint32_t* qp = reinterpret_cast<const uint32_t*>(smem + SM_Q + (id & 127) * 256 + (id >> 7) * 32) + hf;
            const float2 q0 = unpack_f16(qp[0]), q1 = unpack_f16(qp[2]), q2 = unpack_f16(qp[4]), q3 = unpack_f16(qp[6]);
            float mx = -INFINITY, mn = INFINITY;
#pragma unroll
            for (int t = 0; t < 16; t++) {
                float sc = q0.x * bf_lo(kr[t].x) + q0.y * bf_hi(kr[t].x) + q1.x * bf_lo(kr[t].y) + q1.y * bf_hi(kr[t].y) +
                           q2.x * bf_lo(kr[t].z) + q2.y * bf_hi(kr[t].z) + q3.x * bf_lo(kr[t].w) + q3.y * bf_hi(kr[t].w);
                sc += __shfl_xor_sync(0xffffffffu, sc, 1);
                sc *= ssc;
                if (!(sc == sc)) sc = INFINITY;
                mx = fmaxf(mx, sc);
                mn = fminf(mn, sc);
            }
#pragma unroll
            for (int o = 16; o > 1; o >>= 1) {
                mx = fmaxf(mx, __shfl_xor_sync(0xffffffffu, mx, o));
                mn = fminf(mn, __shfl_xor_sync(0xffffffffu, mn, o));
            }
            if (lane == 0) { atomicMax(&l_mx[e], f2ord(mx)); atomicMin(&l_mn[e], f2ord(mn)); }
        }
        __syncthreads();
        for (int e = tid; e < n_list; e += A_NTH) {
            const float n = reinterpret_cast<const float*>(smem + SM_N)[l_id[e]];
            const float slack = 0.02f + sqrt_approx(n) * kmaxn * 0.002f;
            if (!(ord2f(l_mx[e]) + slack <= A_HI) || !(ord2f(l_mn[e]) - slack >= A_LO) || !(slack < 0.25f)) s_bad[l_id[e]] = 1;
        }
        __syncthreads();
    }

    const uint32_t sK = smem_u32(smem + SM_K), sV = smem_u32(smem + SM_V);
    uint32_t badmask = 0;
    TL(1, 3);
#pragma unroll 1
    for (int hp = 0; hp < 4; hp++) {
        const unsigned char* sq = smem + SM_Q + rloc * 256 + hp * 64 + t4 * 8;
        uint32_t qA[4], qB[4];
        {
            uint2 a0 = *reinterpret_cast<const uint2*>(sq), a1 = *reinterpret_cast<const uint2*>(sq + 8 * 256);
            uint2 b0 = *reinterpret_cast<const uint2*>(sq + 32), b1 = *reinterpret_cast<const uint2*>(sq + 32 + 8 * 256);
            qA[0] = a0.x; qA[1] = a1.x; qA[2] = a0.y; qA[3] = a1.y;
            qB[0] = b0.x; qB[1] = b1.x; qB[2] = b0.y; qB[3] = b1.y;
        }
        float OA[10], OB[10];
        attn_loop(OA, OB, qA, qB, sK, sV);
        const float4 ib = *reinterpret_cast<const float4*>(s_ib + t4 * 4);
        __nv_bfloat16* dst = &g_O[br][row0][(hg * 8 + hp * 2) * DH + t4 * 4];
        badmask |= finish_rows(OA, s_bad + hp * 256 + rloc, ib, dst) << (hp * 4);
        badmask |= finish_rows(OB, s_bad + hp * 256 + 128 + rloc, ib, dst + DH) << (hp * 4 + 2);
        TL(1, 4 + hp);
    }
    {
        const unsigned qmask = 0xFu << (lane & 28);
        while (badmask) {
            const int b = __ffs(badmask) - 1;
            attn_safe_row(br, row0 + (b & 1) * 8, hg * 8 + (b >> 1), t4, qmask);
            badmask &= badmask - 1;
        }
    }
    __syncthreads();
    if (tid == 0) asm volatile("st.release.gpu.global.u32 [%0], %1;" ::"l"(&g_flag[qb][br * 4 + hg]), "r"(gen2 + 1) : "memory");

    {
        const int cb = br * 4 + hg;
        auto chunk_of = [&](int i) { return ((br ^ (i >> 3)) << 3) + (((hg + (i >> 1)) & 3) << 1) + (i & 1); };
        auto load = [&](int i) {
            const int ch = chunk_of(i);
            const uint32_t sa = sbase + (i % O_ASTAGES) * G_ABYTES;
            const __nv_bfloat16* A = &g_O[ch >> 3][qb * 128][(ch & 7) * 64];
#pragma unroll
            for (int j = 0; j < 4; j++) {
                const int r = warp * 16 + j * 4 + r4;
                cp_async16(sa + r * 128 + ((c8 ^ (r & 7)) << 4), A + (size_t)r * DM + c8 * 8);
            }
            cp_commit();
        };
#pragma unroll
        for (int i = 0; i < 16; i++) {
            const int ch = chunk_of(i);
            const __nv_bfloat16* W = ((ch >> 3) ? prm.wo[1] : prm.wo[0]) + cb * 64;
#pragma unroll
            for (int j = 0; j < 2; j++) {
                const int kr = warp * 8 + j * 4 + r4;
                cp_async16(sbase + O_BOFF + i * G_BBLK + kr * 128 + ((c8 ^ (kr & 7)) << 4), W + (size_t)((ch & 7) * 64 + kr) * DM + c8 * 8);
            }
            if (i == 1) load(0);
        }
        load(1);
        float gt0 = 0.f, gt1 = 0.f;
        float acc0[32], acc1[32];
#pragma unroll
        for (int i = 0; i < 32; i++) { acc0[i] = 0.f; acc1[i] = 0.f; }
#pragma unroll
        for (int i = 0; i < 16; i++) {
            if (i == 0) { if (tid < 8) bar_wait(&g_flag[qb][tid], gen2 + 1); cp_wait<1>(); }
            else if (i == 1) cp_wait<O_ASTAGES - 2>(); else cp_wait<O_ASTAGES - 3>();
            fence_async_proxy();
            __syncthreads();
            if (i == 0) {
                TL(2, 1);
                load(2); load(3); load(4);
                gt0 = __ldcg(&g_gate[row0]); gt1 = __ldcg(&g_gate[row0 + 8]);
            }
            if (i >= 2) { if (i + 3 < 16) load(i + 3); else cp_commit(); }
            const uint32_t sa = sbase + (i % O_ASTAGES) * G_ABYTES + wg * 8192, sb = sbase + O_BOFF + i * G_BBLK;
            WG_FENCE();
#pragma unroll
            for (int kk = 0; kk < 4; kk++) wg_bf16_n64(i < 8 ? acc0 : acc1, mkdesc_sw128(sa + kk * 32, 1), mkdesc_sw128(sb + kk * 2048, G_BBLK / 16));
            WG_COMMIT();
            WG_WAIT(1);
        }
        WG_WAIT(0);
        fence_regs<32>(acc0);
        fence_regs<32>(acc1);
        TL(2, 2);
        unsigned char* st = smem + O_BOFF + warp * (16 * 144);
#pragma unroll
        for (int h = 0; h < 2; h++) {
            const float gt = h ? gt1 : gt0;
            const float og = bf16_round(1.f - gt);
            const float w0 = br ? og : gt, w1 = br ? gt : og;
#pragma unroll
            for (int j = 0; j < 8; j++) {
                const uint32_t pa = pack_bf16(acc0[4 * j + 2 * h], acc0[4 * j + 2 * h + 1]);
                const uint32_t pb = pack_bf16(acc1[4 * j + 2 * h], acc1[4 * j + 2 * h + 1]);
                const uint32_t ta = pack_bf16(w0 * bf_lo(pa), w0 * bf_hi(pa));
                const uint32_t tb = pack_bf16(w1 * bf_lo(pb), w1 * bf_hi(pb));
                *reinterpret_cast<uint32_t*>(st + (g + h * 8) * 144 + j * 16 + t4 * 4) = pack_bf16(bf_lo(ta) + bf_lo(tb), bf_hi(ta) + bf_hi(tb));
            }
        }
        __syncwarp();
#pragma unroll
        for (int j = 0; j < 4; j++) {
            const int r = j * 4 + r4;
            const uint4 v = *reinterpret_cast<const uint4*>(st + r * 144 + c8 * 16);
            *reinterpret_cast<uint4*>(prm.out + (size_t)(qb * 128 + warp * 16 + r) * DM + cb * 64 + c8 * 8) = v;
        }
        TL(2, 3);
    }
}

}

extern "C" void kernel_launch(void* const* d_in, const int* in_sizes, int n_in, void* d_out, int out_size) {
    Params prm;
    prm.x = (const __nv_bfloat16*)d_in[0];
    for (int b = 0; b < 2; b++) {
        prm.wq[b] = (const __nv_bfloat16*)d_in[1 + 5 * b];
        prm.wk[b] = (const __nv_bfloat16*)d_in[2 + 5 * b];
        prm.wv[b] = (const __nv_bfloat16*)d_in[3 + 5 * b];
        prm.wo[b] = (const __nv_bfloat16*)d_in[4 + 5 * b];
    }
    prm.gate_w = (const __nv_bfloat16*)d_in[10];
    prm.out = (__nv_bfloat16*)d_out;

    static bool attr_set = false;
    if (!attr_set) {
        cudaFuncSetAttribute(fused_kernel, cudaFuncAttributeMaxDynamicSharedMemorySize, SM_TOTAL);
        attr_set = true;
    }
    cudaLaunchAttribute at[1];
    at[0].id = cudaLaunchAttributeCooperative;
    at[0].val.cooperative = 1;
    cudaLaunchConfig_t cfg = {};
    cfg.gridDim = dim3(128);
    cfg.blockDim = dim3(A_NTH);
    cfg.dynamicSmemBytes = SM_TOTAL;
    cfg.stream = cudaStreamPerThread;
    cfg.attrs = at;
    cfg.numAttrs = 1;
    cudaLaunchKernelEx(&cfg, fused_kernel, prm);
}
```

```cpp
#include <cuda_runtime.h>
#include <cuda_bf16.h>
#include <cuda_fp16.h>
#include <stdint.h>
#include <limits.h>

namespace {

constexpr int S_LEN = 2048;
constexpr int DM = 512;
constexpr int DH = 16;

__device__ __align__(128) __nv_bfloat16 g_K[2][S_LEN][DH];
__device__ __align__(128) __nv_bfloat16 g_V[2][S_LEN][DH];
__device__ __align__(128) __nv_bfloat16 g_O[2][S_LEN][DM];
__device__ float g_gate[S_LEN];
__device__ uint32_t g_stat[2][2][32];
__device__ unsigned int g_bar[2][32];
__device__ unsigned int g_flag[16][8];

#define TL(k, i)
__device__ __forceinline__ uint32_t smem_u32(const void* p) { return (uint32_t)__cvta_generic_to_shared(p); }
__device__ __forceinline__ void cp_async16(uint32_t dst, const void* src) {
    asm volatile("cp.async.cg.shared.global [%0], [%1], 16;" ::"r"(dst), "l"(src));
}
__device__ __forceinline__ void cp_commit() { asm volatile("cp.async.commit_group;"); }
template <int N> __device__ __forceinline__ void cp_wait() { asm volatile("cp.async.wait_group %0;" ::"n"(N) : "memory"); }
__device__ __forceinline__ void fence_async_proxy() { asm volatile("fence.proxy.async.shared::cta;" ::: "memory"); }
__device__ __forceinline__ float bf16_round(float x) { return __bfloat162float(__float2bfloat16_rn(x)); }
__device__ __forceinline__ uint32_t pack_bf16(float lo, float hi) {
    uint32_t p;
    asm("cvt.rn.bf16x2.f32 %0, %1, %2;" : "=r"(p) : "f"(hi), "f"(lo));
    return p;
}
__device__ __forceinline__ float bf_lo(uint32_t v) { return __uint_as_float(v << 16); }
__device__ __forceinline__ float bf_hi(uint32_t v) { return __uint_as_float(v & 0xffff0000u); }
__device__ __forceinline__ uint32_t pack_f16(float lo, float hi) {
    uint32_t p;
    asm("cvt.rn.f16x2.f32 %0, %1, %2;" : "=r"(p) : "f"(hi), "f"(lo));
    return p;
}
__device__ __forceinline__ uint32_t pack_f16_sat(float lo, float hi) {
    uint32_t p;
    asm("cvt.rn.satfinite.f16x2.f32 %0, %1, %2;" : "=r"(p) : "f"(hi), "f"(lo));
    return p;
}
__device__ __forceinline__ float2 unpack_f16(uint32_t v) { return __half22float2(*reinterpret_cast<__half2*>(&v)); }
__device__ __forceinline__ float rcp_approx(float x) { float r; asm("rcp.approx.ftz.f32 %0, %1;" : "=f"(r) : "f"(x)); return r; }
__device__ __forceinline__ float sqrt_approx(float x) { float r; asm("sqrt.approx.ftz.f32 %0, %1;" : "=f"(r) : "f"(x)); return r; }

#define WG_FENCE() asm volatile("wgmma.fence.sync.aligned;" ::: "memory")
#define WG_COMMIT() asm volatile("wgmma.commit_group.sync.aligned;" ::: "memory")
#define WG_WAIT(n) asm volatile("wgmma.wait_group.sync.aligned " #n ";" ::: "memory")
#define R8(b) "+f"(d[b + 0]), "+f"(d[b + 1]), "+f"(d[b + 2]), "+f"(d[b + 3]), "+f"(d[b + 4]), "+f"(d[b + 5]), "+f"(d[b + 6]), "+f"(d[b + 7])

__device__ __forceinline__ uint64_t mkdesc(uint32_t saddr, uint32_t sbo16, uint32_t lbo16 = 8) {
    uint32_t lo = ((saddr & 0x3FFFF) >> 4) | (lbo16 << 16);
    uint64_t d;
    asm("mov.b64 %0, {%1, %2};" : "=l"(d) : "r"(lo), "r"(sbo16));
    return d;
}
__device__ __forceinline__ uint64_t mkdesc_sw128(uint32_t saddr, uint32_t lbo16) {
    uint32_t lo = ((saddr & 0x3FFFF) >> 4) | (lbo16 << 16);
    uint64_t d;
    asm("mov.b64 %0, {%1, %2};" : "=l"(d) : "r"(lo), "r"(0x40000040u));
    return d;
}
template <int N> __device__ __forceinline__ void fence_regs(float* D) {
#pragma unroll
    for (int i = 0; i < N; i++) asm volatile("" : "+f"(D[i])::"memory");
}

__device__ __forceinline__ void wg_bf16_n64(float* d, uint64_t da, uint64_t db) {
    asm volatile(
        "wgmma.mma_async.sync.aligned.m64n64k16.f32.bf16.bf16 "
        "{%0,%1,%2,%3,%4,%5,%6,%7,%8,%9,%10,%11,%12,%13,%14,%15,%16,%17,%18,%19,%20,%21,%22,%23,%24,%25,%26,%27,%28,%29,%30,%31},"
        " %32, %33, 1, 1, 1, 0, 1;"
        : R8(0), R8(8), R8(16), R8(24)
        : "l"(da), "l"(db));
}
__device__ __forceinline__ void wg_bf16_n144(float* d, uint64_t da, uint64_t db) {
    asm volatile(
        "wgmma.mma_async.sync.aligned.m64n144k16.f32.bf16.bf16 "
        "{%0,%1,%2,%3,%4,%5,%6,%7,%8,%9,%10,%11,%12,%13,%14,%15,%16,%17,%18,%19,%20,%21,%22,%23,%24,%25,%26,%27,%28,%29,%30,%31,"
        "%32,%33,%34,%35,%36,%37,%38,%39,%40,%41,%42,%43,%44,%45,%46,%47,%48,%49,%50,%51,%52,%53,%54,%55,%56,%57,%58,%59,%60,%61,%62,%63,"
        "%64,%65,%66,%67,%68,%69,%70,%71}, %72, %73, 1, 1, 1, 0, 1;"
        : R8(0), R8(8), R8(16), R8(24), R8(32), R8(40), R8(48), R8(56), R8(64)
        : "l"(da), "l"(db));
}

constexpr int G_ABYTES = 128 * 128;
constexpr int G_BBLK = 64 * 128;
constexpr int P_STAGES = 5;
constexpr int P_STAGE = G_ABYTES + 3 * G_BBLK;
constexpr int O_ASTAGES = 5;
constexpr int O_BOFF = O_ASTAGES * G_ABYTES;

__device__ __forceinline__ unsigned int ld_acquire(const unsigned int* p) {
    unsigned int v;
    asm volatile("ld.acquire.gpu.global.u32 %0, [%1];" : "=r"(v) : "l"(p) : "memory");
    return v;
}
__device__ __forceinline__ unsigned int ld_relaxed(const unsigned int* p) {
    unsigned int v;
    asm volatile("ld.relaxed.gpu.global.u32 %0, [%1];" : "=r"(v) : "l"(p) : "memory");
    return v;
}
__device__ __forceinline__ void bar_arrive(int id) {
    asm volatile("red.release.gpu.global.add.u32 [%0], 1;" ::"l"(&g_bar[id][0]) : "memory");
}
__device__ __forceinline__ void bar_wait(const unsigned int* p, unsigned int target) {
    long long t0 = clock64();
    while ((int)(ld_acquire(p) - target) < 0) {
        if (clock64() - t0 > 4000000000ll) __trap();
    }
}

#define ATT_POLY 1
#define ATT_MASK 0x2828
constexpr int A_NT = 128;
constexpr int A_NTH = 256;
constexpr uint32_t A_MASK = ATT_MASK;
__host__ __device__ constexpr int popc16(uint32_t m) { int c = 0; for (int i = 0; i < 16; i++) c += (m >> i) & 1; return c; }
constexpr int A_NM = 8 * popc16(A_MASK);
constexpr int A_NP = A_NT - A_NM;
constexpr float A_F0 = (ATT_POLY == 1) ? (15.f - 0.59368f) : (16.f - 1.71838f);
constexpr float A_MUS = (ATT_POLY == 1) ? 1.f : 2.f;
constexpr float A_LO = -A_F0 + 0.1f;
constexpr float A_HI = ((ATT_POLY == 1) ? 29.9f : 28.9f) - A_F0;
constexpr float A_BMAX = (-A_LO < A_HI) ? -A_LO : A_HI;
#define ATT_FL 4
constexpr int A_FL = ATT_FL;
constexpr float A_VS = 1.f / (256.f * A_FL);
constexpr float A_LMIN = 32.f * A_VS;
constexpr float A_C = 0.25f * 1.4426950408889634f;

constexpr int SM_K = 0;
constexpr int SM_V = 65536;
constexpr int SM_Q = SM_V + 98304;
constexpr int SM_N = SM_Q + 32768;
constexpr int SM_B = SM_N + 4096;
constexpr int SM_S = SM_B + 1024;
constexpr int SM_L = SM_S + 128;
constexpr int SM_TOTAL = O_BOFF + 16 * G_BBLK;
static_assert(P_STAGES * P_STAGE <= SM_TOTAL && SM_L + 2048 + 8192 <= SM_TOTAL, "smem");

__device__ __forceinline__ void bump(uint64_t& d, uint32_t inc16) {
    asm volatile("{.reg .b32 lo, hi; mov.b64 {lo, hi}, %0; add.u32 lo, lo, %1; mov.b64 %0, {lo, hi};}" : "+l"(d) : "r"(inc16));
}
__device__ __forceinline__ void wg_qk128(float* d, const uint32_t* a, uint64_t desc) {
    asm volatile(
        "wgmma.mma_async.sync.aligned.m64n128k16.f32.f16.f16 "
        "{%0,%1,%2,%3,%4,%5,%6,%7,%8,%9,%10,%11,%12,%13,%14,%15,%16,%17,%18,%19,%20,%21,%22,%23,%24,%25,%26,%27,%28,%29,%30,%31,"
        "%32,%33,%34,%35,%36,%37,%38,%39,%40,%41,%42,%43,%44,%45,%46,%47,%48,%49,%50,%51,%52,%53,%54,%55,%56,%57,%58,%59,%60,%61,%62,%63},"
        " {%64,%65,%66,%67}, %68, 1, 1, 1, 0;"
        : R8(0), R8(8), R8(16), R8(24), R8(32), R8(40), R8(48), R8(56)
        : "r"(a[0]), "r"(a[1]), "r"(a[2]), "r"(a[3]), "l"(desc));
}
__device__ __forceinline__ void wg_pv24h(uint32_t* d, const uint32_t* a, uint64_t desc) {
    asm volatile(
        "wgmma.mma_async.sync.aligned.m64n24k16.f16.f16.f16 {%0,%1,%2,%3,%4,%5}, {%6,%7,%8,%9}, %10, 1, 1, 1, 1;"
        : "+r"(d[0]), "+r"(d[1]), "+r"(d[2]), "+r"(d[3]), "+r"(d[4]), "+r"(d[5])
        : "r"(a[0]), "r"(a[1]), "r"(a[2]), "r"(a[3]), "l"(desc));
}
__device__ __forceinline__ uint32_t poly_pair(float y0, float y1) {
    uint32_t z, w, t;
    asm("prmt.b32 %0, %1, %2, 0x6521;" : "=r"(z) : "f"(y0), "f"(y1));
    asm("lop3.b32 %0, %1, 0x03ff03ff, 0x38003800, 0xEA;" : "=r"(w) : "r"(z));
    asm("fma.rn.f16x2 %0, %1, %1, %2;" : "=r"(t) : "r"(w), "r"(0x380b380b));
    return z + t - w;
}
__device__ __forceinline__ uint32_t mufu_pair(float x0, float x1) {
    float a, b;
    asm("ex2.approx.ftz.f32 %0, %1;" : "=f"(a) : "f"(x0));
    asm("ex2.approx.ftz.f32 %0, %1;" : "=f"(b) : "f"(x1));
    return pack_f16(a, b);
}
template <int J0, int J1>
__device__ __forceinline__ void exp_block(const float* D, uint32_t* P) {
#pragma unroll
    for (int j = J0; j < J1; j++) {
        const int im = popc16(A_MASK & ((1u << j) - 1)), ip = j - im;
        if ((A_MASK >> j) & 1) {
            P[2 * (j - J0)] = mufu_pair(D[A_NP / 2 + 4 * im], D[A_NP / 2 + 4 * im + 1]);
            P[2 * (j - J0) + 1] = mufu_pair(D[A_NP / 2 + 4 * im + 2], D[A_NP / 2 + 4 * im + 3]);
        } else {
            P[2 * (j - J0)] = poly_pair(D[4 * ip], D[4 * ip + 1]);
            P[2 * (j - J0) + 1] = poly_pair(D[4 * ip + 2], D[4 * ip + 3]);
        }
    }
}

__device__ __forceinline__ float pow2_norm(uint32_t vbits) {
    int e = (int)((vbits >> 23) & 0xff);
    e = min(max(e, 16), 240);
    return __uint_as_float((uint32_t)(253 - e) << 23);
}
__device__ __forceinline__ float pow2_inv(float p) { return __uint_as_float(0x7f000000u - __float_as_uint(p)); }
__device__ __forceinline__ int f2ord(float f) { int i = __float_as_int(f); return i ^ ((i >> 31) & 0x7fffffff); }
__device__ __forceinline__ float ord2f(int i) { return __int_as_float(i ^ ((i >> 31) & 0x7fffffff)); }

__device__ __noinline__ void attn_safe_row(const uint32_t* qs, float ssc, int br, int row, int head, int t4, unsigned qmask) {
    float q[DH], o[DH];
#pragma unroll
    for (int t = 0; t < 4; t++) {
        const float2 a = unpack_f16(qs[2 * t]), b = unpack_f16(qs[2 * t + 1]);
        q[2 * t] = a.x * ssc; q[2 * t + 1] = a.y * ssc; q[8 + 2 * t] = b.x * ssc; q[9 + 2 * t] = b.y * ssc;
    }
#pragma unroll
    for (int d = 0; d < DH; d++) o[d] = 0.f;
    float m = -INFINITY, l = 0.f;
    for (int j = t4; j < S_LEN; j += 4) {
        uint4 k0 = *reinterpret_cast<const uint4*>(&g_K[br][j][0]);
        uint4 k1 = *reinterpret_cast<const uint4*>(&g_K[br][j][8]);
        uint4 v0 = *reinterpret_cast<const uint4*>(&g_V[br][j][0]);
        uint4 v1 = *reinterpret_cast<const uint4*>(&g_V[br][j][8]);
        const uint32_t kk[8] = {k0.x, k0.y, k0.z, k0.w, k1.x, k1.y, k1.z, k1.w};
        const uint32_t vv[8] = {v0.x, v0.y, v0.z, v0.w, v1.x, v1.y, v1.z, v1.w};
        float s = 0.f;
#pragma unroll
        for (int d = 0; d < 8; d++) s += q[2 * d] * bf_lo(kk[d]) + q[2 * d + 1] * bf_hi(kk[d]);
        float mn = fmaxf(m, s);
        float c = exp2f(m - mn), p = exp2f(s - mn);
        if (mn == -INFINITY) { c = 1.f; p = 0.f; }
        l = l * c + p;
#pragma unroll
        for (int d = 0; d < 8; d++) {
            o[2 * d] = o[2 * d] * c + p * bf_lo(vv[d]);
            o[2 * d + 1] = o[2 * d + 1] * c + p * bf_hi(vv[d]);
        }
        m = mn;
    }
    float mm = fmaxf(m, __shfl_xor_sync(qmask, m, 1));
    mm = fmaxf(mm, __shfl_xor_sync(qmask, mm, 2));
    float c = (mm == -INFINITY) ? 1.f : exp2f(m - mm);
    l *= c;
    l += __shfl_xor_sync(qmask, l, 1);
    l += __shfl_xor_sync(qmask, l, 2);
    float inv = 1.f / l;
    __nv_bfloat16* op = &g_O[br][row][head * DH];
#pragma unroll
    for (int d = 0; d < DH; d++) {
        float v = o[d] * c;
        v += __shfl_xor_sync(qmask, v, 1);
        v += __shfl_xor_sync(qmask, v, 2);
        if ((d >> 2) == t4) op[d] = __float2bfloat16_rn(v * inv);
    }
}

__device__ __forceinline__ void flush_acc(float* O, uint32_t* H) {
#pragma unroll
    for (int i = 0; i < 6; i++) asm volatile("" : "+r"(H[i])::"memory");
#pragma unroll
    for (int i = 0; i < 4; i++) { float2 f = unpack_f16(H[i]); O[2 * i] += f.x; O[2 * i + 1] += f.y; }
    O[8] += unpack_f16(H[4]).x;
    O[9] += unpack_f16(H[5]).x;
#pragma unroll
    for (int i = 0; i < 6; i++) H[i] = 0u;
}

__device__ __forceinline__ void attn_loop(float* OA, float* OB, const uint32_t* qA, const uint32_t* qB, uint32_t sK, uint32_t sV) {
    float DA[64], DB[64];
    uint32_t P0[16], P1[16];
    uint32_t HA[6] = {0u, 0u, 0u, 0u, 0u, 0u}, HB[6] = {0u, 0u, 0u, 0u, 0u, 0u};
#pragma unroll
    for (int i = 0; i < 64; i++) DA[i] = DB[i] = (i < A_NP / 2) ? 2.f + A_F0 * 0.0625f + 3.0517578125e-5f : 0.f;
#pragma unroll
    for (int i = 0; i < 10; i++) OA[i] = OB[i] = 0.f;
    uint64_t dpA = mkdesc(sK, 16), dpB = mkdesc(sK, 16);
    uint64_t dv[8];
#pragma unroll
    for (int j = 0; j < 8; j++) dv[j] = mkdesc(sV + j * 768, 16);
    WG_FENCE();
    wg_qk128(DA, qA, dpA);
    WG_COMMIT();
    WG_WAIT(0);
    fence_regs<64>(DA);
#pragma unroll 1
    for (int grp = 0; grp < S_LEN / A_NT / A_FL; grp++) {
#pragma unroll 1
        for (int t = 0; t < A_FL; t++) {
            WG_FENCE();
            wg_qk128(DB, qB, dpB);
            WG_COMMIT();
            bump(dpB, A_NT * 2); bump(dpA, A_NT * 2);
            exp_block<0, 8>(DA, P0);
            WG_FENCE();
#pragma unroll
            for (int j = 0; j < 4; j++) wg_pv24h(HA, &P0[4 * j], dv[j]);
            WG_COMMIT();
            WG_WAIT(2);
            exp_block<8, 16>(DA, P1);
            WG_FENCE();
#pragma unroll
            for (int j = 4; j < 8; j++) wg_pv24h(HA, &P1[4 * (j - 4)], dv[j]);
            WG_COMMIT();
            WG_WAIT(1);
            fence_regs<64>(DB);
            WG_FENCE();
            wg_qk128(DA, qA, dpA);
            WG_COMMIT();
            exp_block<0, 8>(DB, P0);
            WG_FENCE();
#pragma unroll
            for (int j = 0; j < 4; j++) { wg_pv24h(HB, &P0[4 * j], dv[j]); bump(dv[j], A_NT * 3); }
            WG_COMMIT();
            WG_WAIT(2);
            exp_block<8, 16>(DB, P1);
            WG_FENCE();
#pragma unroll
            for (int j = 4; j < 8; j++) { wg_pv24h(HB, &P1[4 * (j - 4)], dv[j]); bump(dv[j], A_NT * 3); }
            WG_COMMIT();
            WG_WAIT(1);
            fence_regs<64>(DA);
        }
        flush_acc(OA, HA);
        WG_WAIT(0);
        flush_acc(OB, HB);
    }
}

__device__ __forceinline__ uint32_t finish_rows(const float* O, const unsigned char* flag, const float4 ib, __nv_bfloat16* dst) {
    const bool bad0 = flag[0] || !(O[8] >= A_LMIN && O[8] < 1e30f);
    const bool bad1 = flag[8] || !(O[9] >= A_LMIN && O[9] < 1e30f);
    const float i0 = rcp_approx(O[8]), i1 = rcp_approx(O[9]);
    uint2 a, b;
    a.x = pack_bf16(O[0] * i0 * ib.x, O[1] * i0 * ib.y);
    a.y = pack_bf16(O[4] * i0 * ib.z, O[5] * i0 * ib.w);
    b.x = pack_bf16(O[2] * i1 * ib.x, O[3] * i1 * ib.y);
    b.y = pack_bf16(O[6] * i1 * ib.z, O[7] * i1 * ib.w);
    *reinterpret_cast<uint2*>(dst) = a;
    *reinterpret_cast<uint2*>(dst + 8 * DM) = b;
    return (bad0 ? 1u : 0u) | (bad1 ? 2u : 0u);
}

__device__ __forceinline__ void stash_q(unsigned char* smem, uint2 a, uint2 b, float cq, int h, int rloc, int t4) {
    const uint32_t q0 = pack_f16_sat(bf_lo(a.x) * cq, bf_hi(a.x) * cq), q2 = pack_f16_sat(bf_lo(a.y) * cq, bf_hi(a.y) * cq);
    const uint32_t q1 = pack_f16_sat(bf_lo(b.x) * cq, bf_hi(b.x) * cq), q3 = pack_f16_sat(bf_lo(b.y) * cq, bf_hi(b.y) * cq);
    *reinterpret_cast<uint2*>(smem + SM_Q + rloc * 256 + h * 32 + t4 * 8) = make_uint2(q0, q2);
    *reinterpret_cast<uint2*>(smem + SM_Q + (rloc + 8) * 256 + h * 32 + t4 * 8) = make_uint2(q1, q3);
    const float2 f0 = unpack_f16(q0), f2 = unpack_f16(q2), f1 = unpack_f16(q1), f3 = unpack_f16(q3);
    float n0 = f0.x * f0.x + f0.y * f0.y + f2.x * f2.x + f2.y * f2.y;
    float n1 = f1.x * f1.x + f1.y * f1.y + f3.x * f3.x + f3.y * f3.y;
    n0 += __shfl_xor_sync(0xffffffffu, n0, 1); n0 += __shfl_xor_sync(0xffffffffu, n0, 2);
    n1 += __shfl_xor_sync(0xffffffffu, n1, 1); n1 += __shfl_xor_sync(0xffffffffu, n1, 2);
    float* sn = reinterpret_cast<float*>(smem + SM_N) + h * 128 + rloc;
    if (t4 == 0) { sn[0] = n0; sn[8] = n1; }
}

struct Params {
    const __nv_bfloat16 *x, *wq[2], *wk[2], *wv[2], *wo[2], *gate_w;
    __nv_bfloat16* out;
};

__global__ void __launch_bounds__(A_NTH, 1) fused_kernel(const Params prm) {
    extern __shared__ __align__(1024) unsigned char smem[];
    const int tid = threadIdx.x, lane = tid & 31, warp = tid >> 5;
    const int wg = tid >> 7, warp_in_wg = warp & 3;
    const int br = blockIdx.x >> 6;
    const int qb = (blockIdx.x >> 2) & 15;
    const int hg = blockIdx.x & 3;
    __shared__ uint32_t s_stat[32];
    if (tid < 32) s_stat[tid] = 0u;
    const uint32_t sbase = smem_u32(smem);
    const int c8 = lane & 7, r4 = lane >> 3;
    const int g = lane >> 2, t4 = lane & 3;
    const int rloc = wg * 64 + warp_in_wg * 16 + g;
    const int row0 = qb * 128 + rloc;
    TL(0, 0);
    const unsigned int gen1 = ld_relaxed(&g_bar[br][0]) >> 6, gen2 = ld_relaxed(&g_flag[qb][br * 4 + hg]);
    uint32_t* stat = g_stat[gen1 & 1][br];

    const int grow = qb * 128 + (br * 4 + hg) * 16 + warp * 2;
    uint4 gw0, gw1, gx[2][2];
    uint2 qpk[8][2];
    {
        const __nv_bfloat16* A = prm.x + (size_t)qb * 128 * DM;
        const __nv_bfloat16* Wq = (br ? prm.wq[1] : prm.wq[0]) + hg * 128;
        const __nv_bfloat16* Wx = (hg == 1) ? (br ? prm.wv[1] : prm.wv[0]) : (br ? prm.wk[1] : prm.wk[0]);
        auto load = [&](int chunk) {
            const uint32_t sa = sbase + (chunk % P_STAGES) * P_STAGE, sb = sa + G_ABYTES;
            const int k0 = chunk * 64;
#pragma unroll
            for (int i = 0; i < 4; i++) {
                const int r = warp * 16 + i * 4 + r4;
                cp_async16(sa + r * 128 + ((c8 ^ (r & 7)) << 4), A + (size_t)r * DM + k0 + c8 * 8);
            }
#pragma unroll
            for (int i = 0; i < 4; i++) {
                const int kr = warp * 8 + i * 2 + (lane >> 4), nb = (lane >> 3) & 1;
                cp_async16(sb + nb * G_BBLK + kr * 128 + ((c8 ^ (kr & 7)) << 4), Wq + (size_t)(k0 + kr) * DM + nb * 64 + c8 * 8);
            }
            if (lane < 16) {
                const int kr = warp * 8 + (lane >> 1), c = lane & 1;
                cp_async16(sb + 2 * G_BBLK + kr * 128 + ((c ^ (kr & 7)) << 4), Wx + (size_t)(k0 + kr) * DH + c * 8);
            }
            cp_commit();
        };
#pragma unroll
        for (int c = 0; c < P_STAGES; c++) load(c);
        gw0 = *reinterpret_cast<const uint4*>(prm.gate_w + lane * 8);
        gw1 = *reinterpret_cast<const uint4*>(prm.gate_w + 256 + lane * 8);
#pragma unroll
        for (int r = 0; r < 2; r++) {
            gx[r][0] = *reinterpret_cast<const uint4*>(prm.x + (size_t)(grow + r) * DM + lane * 8);
            gx[r][1] = *reinterpret_cast<const uint4*>(prm.x + (size_t)(grow + r) * DM + 256 + lane * 8);
        }
        float acc[72];
#pragma unroll
        for (int i = 0; i < 72; i++) acc[i] = 0.f;
#pragma unroll
        for (int c = 0; c < 8; c++) {
            if (c == 0) cp_wait<P_STAGES - 1>(); else if (c == 1) cp_wait<P_STAGES - 2>(); else cp_wait<P_STAGES - 3>();
            fence_async_proxy();
            __syncthreads();
            if (c >= 2) { if (c - 2 + P_STAGES < 8) load(c - 2 + P_STAGES); else cp_commit(); }
            const uint32_t sa = sbase + (c % P_STAGES) * P_STAGE + wg * 8192, sb = sbase + (c % P_STAGES) * P_STAGE + G_ABYTES;
            WG_FENCE();
#pragma unroll
            for (int kk = 0; kk < 4; kk++) wg_bf16_n144(acc, mkdesc_sw128(sa + kk * 32, 1), mkdesc_sw128(sb + kk * 2048, G_BBLK / 16));
            WG_COMMIT();
            WG_WAIT(1);
        }
        WG_WAIT(0);
        fence_regs<72>(acc);
        TL(0, 1);
        if (hg < 2) {
            const uint32_t p0 = pack_bf16(acc[64], acc[65]), p1 = pack_bf16(acc[66], acc[67]);
            const uint32_t p2 = pack_bf16(acc[68], acc[69]), p3 = pack_bf16(acc[70], acc[71]);
            __nv_bfloat16* dst = hg ? &g_V[br][0][0] : &g_K[br][0][0];
            *reinterpret_cast<uint32_t*>(dst + row0 * DH + 2 * t4) = p0;
            *reinterpret_cast<uint32_t*>(dst + row0 * DH + 8 + 2 * t4) = p2;
            *reinterpret_cast<uint32_t*>(dst + (row0 + 8) * DH + 2 * t4) = p1;
            *reinterpret_cast<uint32_t*>(dst + (row0 + 8) * DH + 8 + 2 * t4) = p3;
            if (hg == 0) {
                float n0 = bf_lo(p0) * bf_lo(p0) + bf_hi(p0) * bf_hi(p0) + bf_lo(p2) * bf_lo(p2) + bf_hi(p2) * bf_hi(p2);
                float n1 = bf_lo(p1) * bf_lo(p1) + bf_hi(p1) * bf_hi(p1) + bf_lo(p3) * bf_lo(p3) + bf_hi(p3) * bf_hi(p3);
                n0 += __shfl_xor_sync(0xffffffffu, n0, 1); n0 += __shfl_xor_sync(0xffffffffu, n0, 2);
                n1 += __shfl_xor_sync(0xffffffffu, n1, 1); n1 += __shfl_xor_sync(0xffffffffu, n1, 2);
                if (!(n0 <= 3.0e38f)) n0 = 3.0e38f;
                if (!(n1 <= 3.0e38f)) n1 = 3.0e38f;
                float n = fmaxf(n0, n1);
#pragma unroll
                for (int o = 4; o < 32; o <<= 1) n = fmaxf(n, __shfl_xor_sync(0xffffffffu, n, o));
                if (lane == 0) atomicMax(&s_stat[0], __float_as_uint(n));
            } else {
                float v[4] = {fmaxf(fabsf(bf_lo(p0)), fabsf(bf_lo(p1))), fmaxf(fabsf(bf_hi(p0)), fabsf(bf_hi(p1))),
                              fmaxf(fabsf(bf_lo(p2)), fabsf(bf_lo(p3))), fmaxf(fabsf(bf_hi(p2)), fabsf(bf_hi(p3)))};
#pragma unroll
                for (int o = 4; o < 32; o <<= 1)
#pragma unroll
                    for (int i = 0; i < 4; i++) v[i] = fmaxf(v[i], __shfl_xor_sync(0xffffffffu, v[i], o));
                if (lane < 4) {
                    atomicMax(&s_stat[1 + 2 * t4], __float_as_uint(v[0]));
                    atomicMax(&s_stat[2 + 2 * t4], __float_as_uint(v[1]));
                    atomicMax(&s_stat[9 + 2 * t4], __float_as_uint(v[2]));
                    atomicMax(&s_stat[10 + 2 * t4], __float_as_uint(v[3]));
                }
            }
        }
        __syncthreads();
        if (warp == 0) {
            if (hg < 2 && lane < 17 && (hg == 0) == (lane == 0)) atomicMax(&stat[lane], s_stat[lane]);
            __syncwarp();
            if (lane == 0) bar_arrive(br);
        }
#pragma unroll
        for (int h = 0; h < 8; h++) {
            qpk[h][0].x = pack_bf16(acc[8 * h + 0], acc[8 * h + 1]); qpk[h][0].y = pack_bf16(acc[8 * h + 4], acc[8 * h + 5]);
            qpk[h][1].x = pack_bf16(acc[8 * h + 2], acc[8 * h + 3]); qpk[h][1].y = pack_bf16(acc[8 * h + 6], acc[8 * h + 7]);
            stash_q(smem, qpk[h][0], qpk[h][1], A_C / 16.f, h, rloc, t4);
        }
    }

    unsigned char* s_bad = smem + SM_B;
    float* s_ib = reinterpret_cast<float*>(smem + SM_S);
    int* l_cnt = reinterpret_cast<int*>(smem + SM_S + 64);
    unsigned short* l_id = reinterpret_cast<unsigned short*>(smem + SM_L);
    int* l_mx = reinterpret_cast<int*>(smem + SM_L + 2048);
    int* l_mn = l_mx + 1024;
    reinterpret_cast<uint32_t*>(s_bad)[tid] = 0u;
    TL(0, 2);
    if (warp == 0) {
        if (lane == 0) {
            *l_cnt = 0;
            bar_wait(&g_bar[br][0], (gen1 + 1) << 6);
        }
        __syncwarp();
        s_stat[lane] = __ldcg(&stat[lane]);
    }
    __syncthreads();
    TL(1, 1);
    if ((blockIdx.x & 63) == 0 && tid < 32) g_stat[(gen1 + 1) & 1][br][tid] = 0u;
    const int c = tid >> 1, hf = tid & 1;
    uint4 kr[16], vr[16];
#pragma unroll
    for (int t = 0; t < 16; t++) kr[t] = *reinterpret_cast<const uint4*>(&g_K[br][t * A_NT + c][hf * 8]);
    asm volatile("" ::: "memory");
    {
        const uint32_t wp[8] = {gw0.x, gw0.y, gw0.z, gw0.w, gw1.x, gw1.y, gw1.z, gw1.w};
#pragma unroll
        for (int r = 0; r < 2; r++) {
            const uint32_t xp[8] = {gx[r][0].x, gx[r][0].y, gx[r][0].z, gx[r][0].w, gx[r][1].x, gx[r][1].y, gx[r][1].z, gx[r][1].w};
            float sg = 0.f;
#pragma unroll
            for (int j = 0; j < 8; j++) {
                const uint32_t pr = pack_bf16(bf_lo(xp[j]) * bf_lo(wp[j]), bf_hi(xp[j]) * bf_hi(wp[j]));
                sg += bf_lo(pr);
                sg += bf_hi(pr);
            }
#pragma unroll
            for (int o = 16; o > 0; o >>= 1) sg += __shfl_xor_sync(0xffffffffu, sg, o);
            if (lane == 0) g_gate[grow + r] = bf16_round(rcp_approx(1.f + __expf(-bf16_round(sg))));
        }
    }
    const float kmax = sqrt_approx(__uint_as_float(s_stat[0]));
    const bool renorm = !(kmax >= 0.125f && kmax <= 128.f);
    const float alpha = renorm ? pow2_norm(__float_as_uint(kmax)) : 1.f;
    const float kmaxn = kmax * alpha * 16.04f;
    float beta[8];
#pragma unroll
    for (int i = 0; i < 8; i++) beta[i] = pow2_norm(s_stat[1 + hf * 8 + i]);
    if (tid < 2) {
#pragma unroll
        for (int i = 0; i < 8; i++) s_ib[hf * 8 + i] = pow2_inv(beta[i]);
    }
    if (renorm) {
        const float cq = (A_C / 16.f) * pow2_inv(alpha);
#pragma unroll
        for (int h = 0; h < 8; h++) stash_q(smem, qpk[h][0], qpk[h][1], cq, h, rloc, t4);
        __syncthreads();
    }
    {
        const float lim = (A_BMAX - 0.02f) * (A_BMAX - 0.02f);
        const float4 n4 = reinterpret_cast<const float4*>(smem + SM_N)[tid];
        const float nn[4] = {n4.x, n4.y, n4.z, n4.w};
#pragma unroll
        for (int i = 0; i < 4; i++) {
            if (!(nn[i] * kmaxn * kmaxn <= lim)) {
                const int e = atomicAdd(l_cnt, 1);
                l_id[e] = (unsigned short)(tid * 4 + i); l_mx[e] = INT_MIN; l_mn[e] = INT_MAX;
            }
        }
    }
#pragma unroll
    for (int t = 0; t < 16; t++) vr[t] = *reinterpret_cast<const uint4*>(&g_V[br][t * A_NT + c][hf * 8]);
    TL(1, 2);
    {
        const int j = c >> 3;
        const bool mu = (A_MASK >> j) & 1;
        const int im = __popc(A_MASK & ((1u << j) - 1));
        const int krow8 = mu ? (A_NP / 8 + im) : (j - im);
        const float ksc = mu ? alpha * 16.f : alpha;
        const float vsc = mu ? A_VS * A_MUS : A_VS;
        const uint32_t ones = pack_f16(vsc, vsc);
#pragma unroll
        for (int i = 0; i < 8; i++) beta[i] *= vsc;
        float acc[8];
#pragma unroll
        for (int i = 0; i < 8; i++) acc[i] = 0.f;
        unsigned char* kdst = smem + SM_K + krow8 * 256 + hf * 128 + (c & 7) * 16;
        unsigned char* vdst = smem + SM_V + (c >> 4) * 768 + ((c >> 3) & 1) * 128 + (c & 7) * 16 + hf * 8;
#pragma unroll
        for (int t = 0; t < 16; t++) {
            const uint32_t kk[4] = {kr[t].x, kr[t].y, kr[t].z, kr[t].w};
            uint32_t dd[4];
#pragma unroll
            for (int i = 0; i < 4; i++) {
                dd[i] = pack_f16(bf_lo(kk[i]) * ksc - acc[2 * i], bf_hi(kk[i]) * ksc - acc[2 * i + 1]);
                const float2 f = unpack_f16(dd[i]);
                acc[2 * i] += f.x; acc[2 * i + 1] += f.y;
            }
            *reinterpret_cast<uint4*>(kdst + t * (A_NT * 32)) = make_uint4(dd[0], dd[1], dd[2], dd[3]);
        }
#pragma unroll
        for (int t = 0; t < 16; t++) {
            const uint32_t v0 = pack_f16(bf_lo(vr[t].x) * beta[0], bf_hi(vr[t].x) * beta[1]);
            const uint32_t v1 = pack_f16(bf_lo(vr[t].y) * beta[2], bf_hi(vr[t].y) * beta[3]);
            const uint32_t v2 = pack_f16(bf_lo(vr[t].z) * beta[4], bf_hi(vr[t].z) * beta[5]);
            const uint32_t v3 = pack_f16(bf_lo(vr[t].w) * beta[6], bf_hi(vr[t].w) * beta[7]);
            unsigned char* vb = vdst + t * (A_NT * 48);
            *reinterpret_cast<uint2*>(vb) = make_uint2(v0, v2);
            *reinterpret_cast<uint2*>(vb + 256) = make_uint2(v1, v3);
            *reinterpret_cast<uint2*>(vb + 512) = make_uint2(ones, ones);
        }
    }
    fence_async_proxy();
    __syncthreads();
    const int n_list = *l_cnt;
    if (n_list > 0) {
        const float ssc = 16.f * alpha;
#pragma unroll 1
        for (int e = 0; e < n_list; e++) {
            const int id = l_id[e];
            const uint32_t* qp = reinterpret_cast<const uint32_t*>(smem + SM_Q + (id & 127) * 256 + (id >> 7) * 32) + hf;
            const float2 q0 = unpack_f16(qp[0]), q1 = unpack_f16(qp[2]), q2 = unpack_f16(qp[4]), q3 = unpack_f16(qp[6]);
            float mx = -INFINITY, mn = INFINITY;
#pragma unroll
            for (int t = 0; t < 16; t++) {
                float sc = q0.x * bf_lo(kr[t].x) + q0.y * bf_hi(kr[t].x) + q1.x * bf_lo(kr[t].y) + q1.y * bf_hi(kr[t].y) +
                           q2.x * bf_lo(kr[t].z) + q2.y * bf_hi(kr[t].z) + q3.x * bf_lo(kr[t].w) + q3.y * bf_hi(kr[t].w);
                sc += __shfl_xor_sync(0xffffffffu, sc, 1);
                sc *= ssc;
                if (!(sc == sc)) sc = INFINITY;
                mx = fmaxf(mx, sc);
                mn = fminf(mn, sc);
            }
#pragma unroll
            for (int o = 16; o > 1; o >>= 1) {
                mx = fmaxf(mx, __shfl_xor_sync(0xffffffffu, mx, o));
                mn = fminf(mn, __shfl_xor_sync(0xffffffffu, mn, o));
            }
            if (lane == 0) { atomicMax(&l_mx[e], f2ord(mx)); atomicMin(&l_mn[e], f2ord(mn)); }
        }
        __syncthreads();
        for (int e = tid; e < n_list; e += A_NTH) {
            const float n = reinterpret_cast<const float*>(smem + SM_N)[l_id[e]];
            const float slack = 0.02f + sqrt_approx(n) * kmaxn * 0.002f;
            if (!(ord2f(l_mx[e]) + slack <= A_HI) || !(ord2f(l_mn[e]) - slack >= A_LO) || !(slack < 0.25f)) s_bad[l_id[e]] = 1;
        }
        __syncthreads();
    }

#pragma unroll
    for (int i = 0; i < 4; i++) {
        const int r = tid + (i & 1) * 256;
        const __nv_bfloat16* w = ((i >> 1) ? prm.wo[1] : prm.wo[0]) + (size_t)r * DM + (br * 4 + hg) * 64;
        asm volatile("prefetch.global.L2 [%0];" ::"l"(w));
    }
    const uint32_t sK = smem_u32(smem + SM_K), sV = smem_u32(smem + SM_V);
    uint32_t badmask = 0;
    TL(1, 3);
#pragma unroll 1
    for (int hp = 0; hp < 4; hp++) {
        const unsigned char* sq = smem + SM_Q + rloc * 256 + hp * 64 + t4 * 8;
        uint32_t qA[4], qB[4];
        {
            uint2 a0 = *reinterpret_cast<const uint2*>(sq), a1 = *reinterpret_cast<const uint2*>(sq + 8 * 256);
            uint2 b0 = *reinterpret_cast<const uint2*>(sq + 32), b1 = *reinterpret_cast<const uint2*>(sq + 32 + 8 * 256);
            qA[0] = a0.x; qA[1] = a1.x; qA[2] = a0.y; qA[3] = a1.y;
            qB[0] = b0.x; qB[1] = b1.x; qB[2] = b0.y; qB[3] = b1.y;
        }
        float OA[10], OB[10];
        attn_loop(OA, OB, qA, qB, sK, sV);
        const float4 ib = *reinterpret_cast<const float4*>(s_ib + t4 * 4);
        __nv_bfloat16* dst = &g_O[br][row0][(hg * 8 + hp * 2) * DH + t4 * 4];
        badmask |= finish_rows(OA, s_bad + hp * 256 + rloc, ib, dst) << (hp * 4);
        badmask |= finish_rows(OB, s_bad + hp * 256 + 128 + rloc, ib, dst + DH) << (hp * 4 + 2);
        TL(1, 4 + hp);
    }
    {
        const unsigned qmask = 0xFu << (lane & 28);
        while (badmask) {
            const int b = __ffs(badmask) - 1;
            attn_safe_row(reinterpret_cast<const uint32_t*>(smem + SM_Q + (rloc + (b & 1) * 8) * 256 + (b >> 1) * 32), 16.f * alpha, br,
                          row0 + (b & 1) * 8, hg * 8 + (b >> 1), t4, qmask);
            badmask &= badmask - 1;
        }
    }
    __syncthreads();
    if (tid == 0) asm volatile("st.release.gpu.global.u32 [%0], %1;" ::"l"(&g_flag[qb][br * 4 + hg]), "r"(gen2 + 1) : "memory");

    {
        const int cb = br * 4 + hg;
        auto chunk_of = [&](int i) { return ((br ^ (i >> 3)) << 3) + (((hg + (i >> 1)) & 3) << 1) + (i & 1); };
        auto load = [&](int i) {
            const int ch = chunk_of(i);
            const uint32_t sa = sbase + (i % O_ASTAGES) * G_ABYTES;
            const __nv_bfloat16* A = &g_O[ch >> 3][qb * 128][(ch & 7) * 64];
#pragma unroll
            for (int j = 0; j < 4; j++) {
                const int r = warp * 16 + j * 4 + r4;
                cp_async16(sa + r * 128 + ((c8 ^ (r & 7)) << 4), A + (size_t)r * DM + c8 * 8);
            }
            cp_commit();
        };
#pragma unroll
        for (int i = 0; i < 16; i++) {
            const int ch = chunk_of(i);
            const __nv_bfloat16* W = ((ch >> 3) ? prm.wo[1] : prm.wo[0]) + cb * 64;
#pragma unroll
            for (int j = 0; j < 2; j++) {
                const int kr = warp * 8 + j * 4 + r4;
                cp_async16(sbase + O_BOFF + i * G_BBLK + kr * 128 + ((c8 ^ (kr & 7)) << 4), W + (size_t)((ch & 7) * 64 + kr) * DM + c8 * 8);
            }
            if (i == 1) load(0);
        }
        load(1);
        float gt0 = 0.f, gt1 = 0.f;
        float acc0[32], acc1[32];
#pragma unroll
        for (int i = 0; i < 32; i++) { acc0[i] = 0.f; acc1[i] = 0.f; }
#pragma unroll
        for (int i = 0; i < 16; i++) {
            if (i == 0) { if (tid < 8) bar_wait(&g_flag[qb][tid], gen2 + 1); cp_wait<1>(); }
            else if (i == 1) cp_wait<O_ASTAGES - 2>(); else cp_wait<O_ASTAGES - 3>();
            fence_async_proxy();
            __syncthreads();
            if (i == 0) {
                TL(2, 1);
                load(2); load(3); load(4);
                gt0 = __ldcg(&g_gate[row0]); gt1 = __ldcg(&g_gate[row0 + 8]);
            }
            if (i >= 2) { if (i + 3 < 16) load(i + 3); else cp_commit(); }
            const uint32_t sa = sbase + (i % O_ASTAGES) * G_ABYTES + wg * 8192, sb = sbase + O_BOFF + i * G_BBLK;
            WG_FENCE();
#pragma unroll
            for (int kk = 0; kk < 4; kk++) wg_bf16_n64(i < 8 ? acc0 : acc1, mkdesc_sw128(sa + kk * 32, 1), mkdesc_sw128(sb + kk * 2048, G_BBLK / 16));
            WG_COMMIT();
            WG_WAIT(1);
        }
        WG_WAIT(0);
        fence_regs<32>(acc0);
        fence_regs<32>(acc1);
        TL(2, 2);
        unsigned char* st = smem + O_BOFF + warp * (16 * 144);
#pragma unroll
        for (int h = 0; h < 2; h++) {
            const float gt = h ? gt1 : gt0;
            const float og = bf16_round(1.f - gt);
            const float w0 = br ? og : gt, w1 = br ? gt : og;
#pragma unroll
            for (int j = 0; j < 8; j++) {
                const uint32_t pa = pack_bf16(acc0[4 * j + 2 * h], acc0[4 * j + 2 * h + 1]);
                const uint32_t pb = pack_bf16(acc1[4 * j + 2 * h], acc1[4 * j + 2 * h + 1]);
                const uint32_t ta = pack_bf16(w0 * bf_lo(pa), w0 * bf_hi(pa));
                const uint32_t tb = pack_bf16(w1 * bf_lo(pb), w1 * bf_hi(pb));
                *reinterpret_cast<uint32_t*>(st + (g + h * 8) * 144 + j * 16 + t4 * 4) = pack_bf16(bf_lo(ta) + bf_lo(tb), bf_hi(ta) + bf_hi(tb));
            }
        }
        __syncwarp();
#pragma unroll
        for (int j = 0; j < 4; j++) {
            const int r = j * 4 + r4;
            const uint4 v = *reinterpret_cast<const uint4*>(st + r * 144 + c8 * 16);
            *reinterpret_cast<uint4*>(prm.out + (size_t)(qb * 128 + warp * 16 + r) * DM + cb * 64 + c8 * 8) = v;
        }
        TL(2, 3);
    }
}

}

extern "C" void kernel_launch(void* const* d_in, const int* in_sizes, int n_in, void* d_out, int out_size) {
    Params prm;
    prm.x = (const __nv_bfloat16*)d_in[0];
    for (int b = 0; b < 2; b++) {
        prm.wq[b] = (const __nv_bfloat16*)d_in[1 + 5 * b];
        prm.wk[b] = (const __nv_bfloat16*)d_in[2 + 5 * b];
        prm.wv[b] = (const __nv_bfloat16*)d_in[3 + 5 * b];
        prm.wo[b] = (const __nv_bfloat16*)d_in[4 + 5 * b];
    }
    prm.gate_w = (const __nv_bfloat16*)d_in[10];
    prm.out = (__nv_bfloat16*)d_out;

    static bool attr_set = false;
    if (!attr_set) {
        cudaFuncSetAttribute(fused_kernel, cudaFuncAttributeMaxDynamicSharedMemorySize, SM_TOTAL);
        attr_set = true;
    }
    cudaLaunchAttribute at[1];
    at[0].id = cudaLaunchAttributeCooperative;
    at[0].val.cooperative = 1;
    cudaLaunchConfig_t cfg = {};
    cfg.gridDim = dim3(128);
    cfg.blockDim = dim3(A_NTH);
    cfg.dynamicSmemBytes = SM_TOTAL;
    cfg.stream = cudaStreamPerThread;
    cfg.attrs = at;
    cfg.numAttrs = 1;
    cudaLaunchKernelEx(&cfg, fused_kernel, prm);
}
```
